```python
import torch

def _softmax(x, axis=-1):
    return torch.softmax(x, dim=axis)
def _gelu(x):
    return torch.nn.functional.gelu(x, approximate="tanh")
def _silu(x):
    return torch.nn.functional.silu(x)
def _sigmoid(x):
    return torch.sigmoid(x)
def _layernorm(x, axis=-1, eps=1e-5):
    m = x.mean(dim=axis, keepdim=True)
    v = x.var(dim=axis, keepdim=True, unbiased=False)
    return (x - m) / torch.sqrt(v + eps)
def _scatter_add(tgt, idx, src, axis=0):
    return tgt.clone().index_add_(axis, idx, src)
def _segment_sum(src, seg, n):
    out = torch.zeros((n,) + src.shape[1:], dtype=src.dtype)
    return out.index_add_(0, seg, src)
def _pad(x, pw):
    flat = tuple(v for pair in reversed(pw) for v in pair)
    return torch.nn.functional.pad(x, flat)

kernel_name = 'sequential_preLN__spectral_gfnet__mixer_token_mlp__prompt'

def setup_inputs():

    _w = (lambda a: (lambda t: t.to(torch.bfloat16) if t.is_floating_point() else t)(torch.as_tensor(a)))
    def _A_setup():
        B, S, D = 1, 2048, 448
        Df = D // 2 + 1
        return {
            "x": _w((lambda *s: torch.randn(*s, dtype=torch.bfloat16) * 0.05)(B, S, D)),
            "w_r": _w((lambda *s: torch.randn(*s, dtype=torch.bfloat16) * 0.4)(S, Df) * 0.02),
            "w_i": _w((lambda *s: torch.randn(*s, dtype=torch.bfloat16) * 0.4)(S, Df) * 0.02),
        }
    _A_in = _A_setup()

    def _B_setup():
        B, S, D, F = 1, 2048, 448, 1792
        return {
            "x": _w((lambda *s: torch.randn(*s, dtype=torch.bfloat16) * 0.05)(B, S, D)),
            "w1": _w((lambda *s: torch.randn(*s, dtype=torch.bfloat16) * 0.4)(S, F) * (S ** -0.5)),
            "b1": _w((lambda *s: torch.randn(*s, dtype=torch.bfloat16) * 3.2)(F) * 0.02),
            "w2": _w((lambda *s: torch.randn(*s, dtype=torch.bfloat16) * 0.2)(F, S) * (F ** -0.5)),
            "b2": _w((lambda *s: torch.randn(*s, dtype=torch.bfloat16) * 0.4)(S) * 0.02),
        }
    _B_in = _B_setup()

    return {
        "A_x": _A_in["x"],
        "A_w_r": _A_in["w_r"],
        "A_w_i": _A_in["w_i"],
        "B_x": _B_in["x"],
        "B_w1": _B_in["w1"],
        "B_b1": _B_in["b1"],
        "B_w2": _B_in["w2"],
        "B_b2": _B_in["b2"],
    }

def reference(A_x, A_w_r, A_w_i, B_x, B_w1, B_b1, B_w2, B_b2):
    def _A_ref(x, w_r, w_i):
        B, S, D = x.shape
        X = (lambda x, axes=(-2,-1): torch.fft.rfft2(x.float(), dim=axes))(x, axes=(-2, -1))
        W = w_r + 1j * w_i
        X = X * W
        y = (lambda x, s, axes=(-2,-1): torch.fft.irfft2(x, s=s, dim=axes).to(torch.bfloat16))(X, (S, D), axes=(-2, -1))
        return y

    def _B_ref(x, w1, b1, w2, b2):
        B, S, D = x.shape
        h = _layernorm(x, axis=-1)
        u = torch.einsum("bsd,sf->bdf", h, w1) + b1
        u = _gelu(u)
        y = torch.einsum("bdf,fs->bds", u, w2) + b2
        return (lambda x, *d: x.permute(*d))(y, 0, 2, 1)

    x = A_x
    h = x + _A_ref(_layernorm(x, axis=-1), A_w_r, A_w_i)
    h2 = h + _B_ref(_layernorm(h, axis=-1), B_w1, B_b1, B_w2, B_b2)
    return h2
```

```cpp
#include <cuda_runtime.h>
#include <cuda_bf16.h>
#include <cuda_fp16.h>
#include <cuda.h>
#include <stdint.h>

namespace {

constexpr int S_ = 2048, D_ = 448, F_ = 1792, DF_ = 225;
constexpr int ZSTRIDE = 14464;

__device__ __align__(1024) uint8_t  g_X[DF_ * 8192];
__device__ __align__(1024) uint32_t g_Wt[DF_ * 128 * 16];
__device__ __align__(1024) uint8_t  g_Z[128 * ZSTRIDE];
__device__ __align__(1024) uint8_t  g_hn[4 * 256 * 1792];
__device__ __align__(1024) uint8_t  g_h[4 * 256 * 1792];
__device__ __align__(1024) uint8_t  g_g[4 * 28 * 14336];

__device__ __forceinline__ uint32_t s2u(const void* p) { return (uint32_t)__cvta_generic_to_shared(p); }
__device__ __forceinline__ void pdl_trigger() { asm volatile("griddepcontrol.launch_dependents;"); }
__device__ __forceinline__ void pdl_wait() { asm volatile("griddepcontrol.wait;" ::: "memory"); }
__device__ __forceinline__ void mbar_init(uint32_t a, int c) { asm volatile("mbarrier.init.shared::cta.b64 [%0], %1;" ::"r"(a), "r"(c) : "memory"); }
__device__ __forceinline__ void mbar_expect(uint32_t a, uint32_t b) { asm volatile("mbarrier.arrive.expect_tx.shared::cta.b64 _, [%0], %1;" ::"r"(a), "r"(b) : "memory"); }
__device__ __forceinline__ void mbar_arrive(uint32_t a) { asm volatile("mbarrier.arrive.shared::cta.b64 _, [%0];" ::"r"(a) : "memory"); }
__device__ __forceinline__ void mbar_wait(uint32_t a, uint32_t ph) {
    uint32_t ok;
    int it = 0;
    do {
        asm volatile("{.reg .pred p; mbarrier.try_wait.parity.shared::cta.b64 p, [%1], %2; selp.u32 %0,1,0,p;}" : "=r"(ok) : "r"(a), "r"(ph) : "memory");
    } while (!ok && ++it < (1 << 22));
}
__device__ __forceinline__ void mbar_wait_cluster(uint32_t a, uint32_t ph) {
    uint32_t ok;
    int it = 0;
    do {
        asm volatile("{.reg .pred p; mbarrier.try_wait.parity.acquire.cluster.shared::cta.b64 p, [%1], %2; selp.u32 %0,1,0,p;}" : "=r"(ok) : "r"(a), "r"(ph) : "memory");
    } while (!ok && ++it < (1 << 22));
}
__device__ __forceinline__ void fence_mbar_init() { asm volatile("fence.mbarrier_init.release.cluster;" ::: "memory"); }
__device__ __forceinline__ void fence_async_smem() { asm volatile("fence.proxy.async.shared::cta;" ::: "memory"); }
__device__ __forceinline__ void bulk_g2s(uint32_t dst, const void* src, uint32_t bytes, uint32_t mbar) {
    asm volatile("cp.async.bulk.shared::cluster.global.mbarrier::complete_tx::bytes [%0], [%1], %2, [%3];" ::"r"(dst), "l"(src), "r"(bytes), "r"(mbar) : "memory");
}
__device__ __forceinline__ void tma_3d(uint32_t dst, const CUtensorMap* tm, int c0, int c1, int c2, uint32_t mbar) {
    asm volatile("cp.async.bulk.tensor.3d.shared::cluster.global.mbarrier::complete_tx::bytes [%0], [%1, {%3, %4, %5}], [%2];" ::"r"(dst), "l"(tm), "r"(mbar), "r"(c0), "r"(c1), "r"(c2) : "memory");
}
__device__ __forceinline__ void l2_prefetch(const void* p, uint32_t bytes) { asm volatile("cp.async.bulk.prefetch.L2.global [%0], %1;" ::"l"(p), "r"(bytes) : "memory"); }
__device__ __forceinline__ void named_bar(int id, int n) { asm volatile("bar.sync %0, %1;" ::"r"(id), "r"(n) : "memory"); }
__device__ __forceinline__ void wg_fence() { asm volatile("wgmma.fence.sync.aligned;" ::: "memory"); }
__device__ __forceinline__ void wg_commit() { asm volatile("wgmma.commit_group.sync.aligned;" ::: "memory"); }
template <int N> __device__ __forceinline__ void wg_wait() { asm volatile("wgmma.wait_group.sync.aligned %0;" ::"n"(N) : "memory"); }

__device__ __forceinline__ uint64_t mk_desc(uint32_t addr, uint32_t lbo, uint32_t sbo, uint32_t swz) {
    return (uint64_t)((addr & 0x3FFFF) >> 4) | ((uint64_t)(lbo >> 4) << 16) | ((uint64_t)(sbo >> 4) << 32) | ((uint64_t)swz << 62);
}
__device__ __forceinline__ uint32_t pack_h2(float lo, float hi) {
    uint32_t r;
    asm("cvt.rn.f16x2.f32 %0, %1, %2;" : "=r"(r) : "f"(hi), "f"(lo));
    return r;
}
__device__ __forceinline__ uint32_t pack_b2(float lo, float hi) {
    uint32_t r;
    asm("cvt.rn.bf16x2.f32 %0, %1, %2;" : "=r"(r) : "f"(hi), "f"(lo));
    return r;
}
__device__ __forceinline__ float bf_lo(uint32_t v) { return __uint_as_float(v << 16); }
__device__ __forceinline__ float bf_hi(uint32_t v) { return __uint_as_float(v & 0xffff0000u); }
__device__ __forceinline__ void cs2pi(int num, int den, float& c, float& s) {
    if (2 * num >= den) num -= den;
    float a = (float)num * (6.283185307179586f / (float)den);
    c = __cosf(a);
    s = __sinf(a);
}

#define R4(d, o) "+f"(d[o]), "+f"(d[o + 1]), "+f"(d[o + 2]), "+f"(d[o + 3])
#define R8(d, o) R4(d, o), R4(d, o + 4)
#define R16(d, o) R8(d, o), R8(d, o + 8)

#define WGMMA_N32_RS(NAME, TY)                                                                                      \
    template <int SA, int TB>                                                                                       \
    __device__ __forceinline__ void NAME(float (&d)[16], const uint32_t (&a)[4], uint64_t db, int sd) {             \
        asm volatile("{.reg .pred p; setp.ne.b32 p, %21, 0;\n"                                                      \
                     "wgmma.mma_async.sync.aligned.m64n32k16.f32." TY "." TY " "                                    \
                     "{%0,%1,%2,%3,%4,%5,%6,%7,%8,%9,%10,%11,%12,%13,%14,%15}, {%16,%17,%18,%19}, %20, p, %22, 1, %23;}" \
                     : R16(d, 0)                                                                                    \
                     : "r"(a[0]), "r"(a[1]), "r"(a[2]), "r"(a[3]), "l"(db), "r"(sd), "n"(SA), "n"(TB));             \
    }
WGMMA_N32_RS(wg_n32_h, "f16")
WGMMA_N32_RS(wg_n32_b, "bf16")

#define WGMMA_N64_RS(NAME, TY)                                                                                      \
    template <int TB>                                                                                               \
    __device__ __forceinline__ void NAME(float (&d)[32], const uint32_t (&a)[4], uint64_t db, int sd) {             \
        asm volatile("{.reg .pred p; setp.ne.b32 p, %37, 0;\n"                                                      \
                     "wgmma.mma_async.sync.aligned.m64n64k16.f32." TY "." TY " "                                    \
                     "{%0,%1,%2,%3,%4,%5,%6,%7,%8,%9,%10,%11,%12,%13,%14,%15,"                                      \
                     "%16,%17,%18,%19,%20,%21,%22,%23,%24,%25,%26,%27,%28,%29,%30,%31}, {%32,%33,%34,%35}, %36, p, 1, 1, %38;}" \
                     : R16(d, 0), R16(d, 16)                                                                        \
                     : "r"(a[0]), "r"(a[1]), "r"(a[2]), "r"(a[3]), "l"(db), "r"(sd), "n"(TB));                      \
    }
WGMMA_N64_RS(wg_n64_h, "f16")
WGMMA_N64_RS(wg_n64_b, "bf16")

template <int TB>
__device__ __forceinline__ void wg_n112_ss(float (&d)[56], uint64_t da, uint64_t db, int sd) {
    asm volatile("{.reg .pred p; setp.ne.b32 p, %58, 0;\n"
                 "wgmma.mma_async.sync.aligned.m64n112k16.f32.bf16.bf16 "
                 "{%0,%1,%2,%3,%4,%5,%6,%7,%8,%9,%10,%11,%12,%13,%14,%15,"
                 "%16,%17,%18,%19,%20,%21,%22,%23,%24,%25,%26,%27,%28,%29,%30,%31,"
                 "%32,%33,%34,%35,%36,%37,%38,%39,%40,%41,%42,%43,%44,%45,%46,%47,"
                 "%48,%49,%50,%51,%52,%53,%54,%55}, %56, %57, p, 1, 1, 1, %59;}"
                 : R16(d, 0), R16(d, 16), R16(d, 32), R8(d, 48)
                 : "l"(da), "l"(db), "r"(sd), "n"(TB));
}

constexpr float C1 = 0.62348980185873353f, C2 = -0.22252093395631440f, C3 = -0.90096886790241913f;
constexpr float S1 = 0.78183148246802981f, S2 = 0.97492791218182361f, S3 = 0.43388373911755812f;

__global__ void __launch_bounds__(384) k1_rowdft(const __nv_bfloat16* __restrict__ x, const __nv_bfloat16* __restrict__ wr,
                                                 const __nv_bfloat16* __restrict__ wi, const __nv_bfloat16* __restrict__ w1,
                                                 const __nv_bfloat16* __restrict__ w2) {
    __shared__ __align__(1024) uint8_t sT[16384];
    const int tid = threadIdx.x, warp = tid >> 5, lane = tid & 31, cta = blockIdx.x;
    pdl_trigger();
    if (warp < 8) {
        const uint32_t* xr = reinterpret_cast<const uint32_t*>(x + (size_t)(cta * 16 + warp * 2) * D_);
        uint32_t xv[2][7];
#pragma unroll
        for (int rr = 0; rr < 2; rr++)
#pragma unroll
            for (int m = 0; m < 7; m++) xv[rr][m] = __ldg(xr + rr * 224 + m * 32 + lane);
        const int q = warp >> 2, w = warp & 3, g = lane >> 2, t = lane & 3;
        const int ap = 32 * q + 8 * w + g;
        uint32_t af[8][4];
        const float sg = q ? -0.125f : 0.125f;
#pragma unroll
        for (int ks = 0; ks < 8; ks++)
#pragma unroll
            for (int hh = 0; hh < 2; hh++) {
                float c, s;
                cs2pi(((8 * ks + 4 * hh + t) * ap) & 63, 64, c, s);
                af[ks][2 * hh] = pack_h2(c * 0.125f, s * 0.125f);
                af[ks][2 * hh + 1] = pack_h2(-s * sg, c * sg);
            }
        float twc[2][3], tws[2][3];
#pragma unroll
        for (int e = 0; e < 2; e++)
#pragma unroll
            for (int b = 0; b < 3; b++) cs2pi((2 * lane + e) * (b + 1), 448, twc[e][b], tws[e][b]);

        float R[2][2][4], I[2][2][3], sum[2], sq[2];
#pragma unroll
        for (int rr = 0; rr < 2; rr++) {
            float ss = 0.f;
#pragma unroll
            for (int e = 0; e < 2; e++) {
                float v[7];
#pragma unroll
                for (int m = 0; m < 7; m++) {
                    v[m] = e ? bf_hi(xv[rr][m]) : bf_lo(xv[rr][m]);
                    ss = fmaf(v[m], v[m], ss);
                }
                const float s1 = v[1] + v[6], s2 = v[2] + v[5], s3 = v[3] + v[4];
                const float d1 = v[1] - v[6], d2 = v[2] - v[5], d3 = v[3] - v[4];
                R[rr][e][0] = (v[0] + s1) + (s2 + s3);
                R[rr][e][1] = fmaf(C3, s3, fmaf(C2, s2, fmaf(C1, s1, v[0])));
                R[rr][e][2] = fmaf(C1, s3, fmaf(C3, s2, fmaf(C2, s1, v[0])));
                R[rr][e][3] = fmaf(C2, s3, fmaf(C1, s2, fmaf(C3, s1, v[0])));
                I[rr][e][0] = fmaf(S3, d3, fmaf(S2, d2, S1 * d1));
                I[rr][e][1] = fmaf(-S1, d3, fmaf(-S3, d2, S2 * d1));
                I[rr][e][2] = fmaf(S2, d3, fmaf(-S1, d2, S3 * d1));
            }
            sum[rr] = R[rr][0][0] + R[rr][1][0];
            sq[rr] = ss;
        }
#pragma unroll
        for (int o = 16; o > 0; o >>= 1) {
#pragma unroll
            for (int rr = 0; rr < 2; rr++) {
                sum[rr] += __shfl_xor_sync(0xffffffffu, sum[rr], o);
                sq[rr] += __shfl_xor_sync(0xffffffffu, sq[rr], o);
            }
        }
        const uint32_t sTa = s2u(sT);
#pragma unroll
        for (int rr = 0; rr < 2; rr++) {
            const float mean = sum[rr] * (1.f / 448.f);
            const float var = fmaxf(fmaf(-mean, mean, sq[rr] * (1.f / 448.f)), 0.f);
            const float rstd = rsqrtf(var + 1e-5f);
            const int rho = warp * 2 + rr;
            const int nl = 8 * ((rho >> 1) & 1) + 2 * (rho >> 2) + (rho & 1);
            const uint32_t base = sTa + (lane >> 4) * 8192 + nl * 128 + ((((lane & 15) >> 1) ^ (nl & 7)) << 4) + (lane & 1) * 8;
            {
                const float m7 = -7.f * mean * rstd;
                const uint32_t p0 = pack_h2(fmaf(R[rr][0][0], rstd, m7), 0.f), p1 = pack_h2(fmaf(R[rr][1][0], rstd, m7), 0.f);
                asm volatile("st.shared.v2.b32 [%0], {%1,%2};" ::"r"(base), "r"(p0), "r"(p1) : "memory");
            }
#pragma unroll
            for (int b = 0; b < 3; b++) {
                uint32_t p[2];
#pragma unroll
                for (int e = 0; e < 2; e++) {
                    const float c = twc[e][b] * rstd, s = tws[e][b] * rstd;
                    const float tr = fmaf(R[rr][e][b + 1], c, -I[rr][e][b] * s);
                    const float ti = -fmaf(R[rr][e][b + 1], s, I[rr][e][b] * c);
                    p[e] = pack_h2(tr, ti);
                }
                asm volatile("st.shared.v2.b32 [%0], {%1,%2};" ::"r"(base + (b + 1) * 2048), "r"(p[0]), "r"(p[1]) : "memory");
            }
        }
        fence_async_smem();
        named_bar(1, 256);
        float acc[32];
        wg_fence();
#pragma unroll
        for (int ks = 0; ks < 8; ks++) wg_n64_h<0>(acc, af[ks], mk_desc(sTa + (ks >> 2) * 8192 + (ks & 3) * 32, 16, 1024, 1), ks);
        wg_commit();
        wg_wait<0>();
        const int a = cta >> 1;
        const uint32_t off = a * 64 + ((((cta & 1) * 2 + (t >> 1)) ^ ((a >> 1) & 3)) << 4) + (t & 1) * 8;
#pragma unroll
        for (int bp = 0; bp < 4; bp++) {
            const int cidx = ((bp + 3) & 3) * 64 + ap;
            if (bp > 0 || ap <= 32) {
                uint8_t* dst = g_X + (size_t)cidx * 8192 + off;
                uint2 vr = make_uint2(pack_h2(acc[8 * bp + 0], acc[8 * bp + 1]), pack_h2(acc[8 * bp + 4], acc[8 * bp + 5]));
                uint2 vi = make_uint2(pack_h2(acc[8 * bp + 2], acc[8 * bp + 3]), pack_h2(acc[8 * bp + 6], acc[8 * bp + 7]));
                *reinterpret_cast<uint2*>(dst) = vr;
                *reinterpret_cast<uint2*>(dst + 4096) = vi;
            }
        }
    } else {
        const int w = cta >> 5, g = (cta >> 2) & 7, t = cta & 3;
        const int o = g & 1;
        const int p = lane & 1, wl = (warp - 8) * 16 + (lane >> 1);
        uint32_t vr[2][8], vi[2][8];
#pragma unroll
        for (int it = 0; it < 2; it++) {
            const int c = wl + 64 * it;
#pragma unroll
            for (int i = 0; i < 8; i++) {
                const int jj = (i >> 2) * 2 + p, h = (i >> 1) & 1, e = i & 1;
                const int j = 16 * w + g + 8 * h + 64 * (8 * jj + 2 * t + e);
                const size_t el = (size_t)j * DF_ - o + 2 * c;
                vr[it][i] = 0; vi[it][i] = 0;
                if (c < 113) {
                    vr[it][i] = __ldg(reinterpret_cast<const uint32_t*>(wr + el));
                    vi[it][i] = __ldg(reinterpret_cast<const uint32_t*>(wi + el));
                }
            }
        }
        if (tid == 256) {
            const char* p1 = reinterpret_cast<const char*>(w1) + (size_t)cta * 57344;
            const char* p2 = reinterpret_cast<const char*>(w2) + (size_t)cta * 57344;
#pragma unroll
            for (int i = 0; i < 4; i++) l2_prefetch(p1 + i * 14336, 14336);
#pragma unroll
            for (int i = 0; i < 4; i++) l2_prefetch(p2 + i * 14336, 14336);
        }
#pragma unroll
        for (int it = 0; it < 2; it++) {
            const int c = wl + 64 * it;
#pragma unroll
            for (int u = 0; u < 2; u++) {
                const int k = 2 * c + u - o;
                if (k >= 0 && k < DF_) {
                    uint32_t z[8];
#pragma unroll
                    for (int i = 0; i < 8; i++) z[i] = __byte_perm(vr[it][i], vi[it][i], u ? 0x7632 : 0x5410);
                    uint4* dst = reinterpret_cast<uint4*>(g_Wt + ((size_t)k * 128 + cta) * 16 + p * 4);
                    dst[0] = make_uint4(z[0], z[1], z[2], z[3]);
                    dst[2] = make_uint4(z[4], z[5], z[6], z[7]);
                }
            }
        }
    }
}

__global__ void __launch_bounds__(256) k2_col() {
    extern __shared__ __align__(1024) uint8_t k2smem[];
    uint8_t(*sX)[8192] = reinterpret_cast<uint8_t(*)[8192]>(k2smem);
    uint8_t* sG2 = k2smem + 16384;
    uint8_t* sG3 = k2smem + 24576;
    uint4(*sFb)[128] = reinterpret_cast<uint4(*)[128]>(k2smem + 32768);
    uint64_t* sbar = reinterpret_cast<uint64_t*>(k2smem + 49152);
    const int tid = threadIdx.x, q = tid >> 7, tl = tid & 127, w = tl >> 5, lane = tid & 31, g = lane >> 2, t = lane & 3;
    const int cidx = blockIdx.x * 2 + q;
    pdl_trigger();
    if (tid == 0) {
        mbar_init(s2u(&sbar[0]), 1);
        mbar_init(s2u(&sbar[1]), 1);
        fence_mbar_init();
    }
    {
        const int n = tid >> 2, kq = tid & 3;
        uint32_t h2[8], b2[8];
#pragma unroll
        for (int i = 0; i < 8; i++) {
            float v2[2], v3[2];
#pragma unroll
            for (int e = 0; e < 2; e++) {
                const int k = 16 * kq + 2 * i + e;
                float c, s;
                cs2pi(((k & 31) * (n & 31)) & 31, 32, c, s);
                const bool kim = k >= 32, nim = n >= 32;
                v2[e] = (kim == nim) ? c : (kim ? s : -s);
                v3[e] = ((kim == nim) ? c : (kim ? -s : s)) * 0.0625f;
            }
            h2[i] = pack_h2(v2[0], v2[1]);
            b2[i] = pack_b2(v3[0], v3[1]);
        }
#pragma unroll
        for (int u = 0; u < 2; u++) {
            const int off = n * 128 + (((2 * kq + u) ^ (n & 7)) << 4);
            *reinterpret_cast<uint4*>(sG2 + off) = make_uint4(h2[4 * u], h2[4 * u + 1], h2[4 * u + 2], h2[4 * u + 3]);
            *reinterpret_cast<uint4*>(sG3 + off) = make_uint4(b2[4 * u], b2[4 * u + 1], b2[4 * u + 2], b2[4 * u + 3]);
        }
    }
    uint32_t fc[4][4], fs[4][4];
    {
        const float sc = (cidx == 192 || cidx == 224) ? 0.0625f : 0.125f;
#pragma unroll
        for (int ks = 0; ks < 4; ks++) {
            uint32_t bc[4], bs[4];
#pragma unroll
            for (int i = 0; i < 4; i++) {
                const int ap = 16 * w + g + 8 * (i & 1), a = 16 * ks + 2 * t + 8 * (i >> 1);
                float c0, s0, c1, s1;
                cs2pi((a * ap) & 63, 64, c0, s0);
                cs2pi(((a + 1) * ap) & 63, 64, c1, s1);
                fc[ks][i] = pack_h2(c0 * sc, c1 * sc);
                fs[ks][i] = pack_h2(s0 * sc, s1 * sc);
                bc[i] = pack_b2(c0 * 0.125f, c1 * 0.125f);
                bs[i] = pack_b2(s0 * 0.125f, s1 * 0.125f);
            }
            if (q == 0) {
                sFb[ks][tl] = make_uint4(bc[0], bc[1], bc[2], bc[3]);
                sFb[4 + ks][tl] = make_uint4(bs[0], bs[1], bs[2], bs[3]);
            }
        }
    }
    float twc[16], tws[16];
#pragma unroll
    for (int i = 0; i < 16; i++) {
        const int ap = 16 * w + g + 8 * ((i >> 1) & 1), b = 8 * (i >> 2) + 2 * t + (i & 1);
        cs2pi(ap * b, 2048, twc[i], tws[i]);
    }
    fence_async_smem();
    __syncthreads();
    pdl_wait();
    if (cidx >= DF_) return;
    const uint32_t xa = s2u(sX[q]), bar = s2u(&sbar[q]);
    if (tl == 0) {
        mbar_expect(bar, 8192);
        bulk_g2s(xa, g_X + (size_t)cidx * 8192, 8192, bar);
    }
    uint32_t wv[16];
    {
        const int ap = cidx & 63, bp = ((cidx >> 6) + 1) & 3;
        const int kp = ap < 32 ? 7 * ap + bp : 448 - 7 * ap - bp;
        const uint4* wp = reinterpret_cast<const uint4*>(g_Wt + ((size_t)kp * 128 + tl) * 16);
#pragma unroll
        for (int i = 0; i < 4; i++) {
            uint4 v = __ldcg(wp + i);
            wv[4 * i] = v.x; wv[4 * i + 1] = v.y; wv[4 * i + 2] = v.z; wv[4 * i + 3] = v.w;
        }
    }
    mbar_wait(bar, 0);
    float yr[16], yi[16];
    wg_fence();
#pragma unroll
    for (int ks = 0; ks < 4; ks++) {
        const uint64_t dr = mk_desc(xa + ks * 1024, 16, 512, 2), di = mk_desc(xa + 4096 + ks * 1024, 16, 512, 2);
        wg_n32_h<1, 1>(yr, fc[ks], dr, ks);
        wg_n32_h<-1, 1>(yi, fs[ks], dr, ks);
        wg_n32_h<1, 1>(yr, fs[ks], di, 1);
        wg_n32_h<1, 1>(yi, fc[ks], di, 1);
    }
    wg_commit();
    wg_wait<0>();
    uint32_t a2[4][4];
#pragma unroll
    for (int i = 0; i < 16; i += 2) {
        const float r0 = fmaf(yr[i], twc[i], yi[i] * tws[i]), i0 = fmaf(yi[i], twc[i], -yr[i] * tws[i]);
        const float r1 = fmaf(yr[i + 1], twc[i + 1], yi[i + 1] * tws[i + 1]), i1 = fmaf(yi[i + 1], twc[i + 1], -yr[i + 1] * tws[i + 1]);
        a2[i >> 3][(i >> 1) & 3] = pack_h2(r0, r1);
        a2[2 + (i >> 3)][(i >> 1) & 3] = pack_h2(i0, i1);
    }
    float acc[32];
    const uint32_t g2a = s2u(sG2), g3a = s2u(sG3);
    wg_fence();
#pragma unroll
    for (int ks = 0; ks < 4; ks++) wg_n64_h<0>(acc, a2[ks], mk_desc(g2a + ks * 32, 16, 1024, 1), ks);
    wg_commit();
#pragma unroll
    for (int ks = 0; ks < 4; ks++) {
        uint4 c = sFb[ks][tl], s = sFb[4 + ks][tl];
        fc[ks][0] = c.x; fc[ks][1] = c.y; fc[ks][2] = c.z; fc[ks][3] = c.w;
        fs[ks][0] = s.x; fs[ks][1] = s.y; fs[ks][2] = s.z; fs[ks][3] = s.w;
    }
    wg_wait<0>();
#pragma unroll
    for (int i = 0; i < 16; i += 2) {
        float zr[2], zi[2];
#pragma unroll
        for (int e = 0; e < 2; e++) {
            const float wre = bf_lo(wv[i + e]), wim = bf_hi(wv[i + e]);
            const float xr_ = acc[i + e], xi_ = acc[16 + i + e];
            zr[e] = fmaf(xr_, wre, -xi_ * wim);
            zi[e] = fmaf(xr_, wim, xi_ * wre);
        }
        a2[i >> 3][(i >> 1) & 3] = pack_b2(zr[0], zr[1]);
        a2[2 + (i >> 3)][(i >> 1) & 3] = pack_b2(zi[0], zi[1]);
    }
    wg_fence();
#pragma unroll
    for (int ks = 0; ks < 4; ks++) wg_n64_b<0>(acc, a2[ks], mk_desc(g3a + ks * 32, 16, 1024, 1), ks);
    wg_commit();
    wg_wait<0>();
    {
        uint32_t pr[2][4], pi[2][4];
#pragma unroll
        for (int i = 0; i < 16; i += 2) {
            const float r0 = fmaf(acc[i], twc[i], -acc[16 + i] * tws[i]), i0 = fmaf(acc[16 + i], twc[i], acc[i] * tws[i]);
            const float r1 = fmaf(acc[i + 1], twc[i + 1], -acc[17 + i] * tws[i + 1]), i1 = fmaf(acc[17 + i], twc[i + 1], acc[i + 1] * tws[i + 1]);
            pr[(i >> 1) & 1][i >> 2] = pack_b2(r0, r1);
            pi[(i >> 1) & 1][i >> 2] = pack_b2(i0, i1);
        }
#pragma unroll
        for (int h = 0; h < 2; h++) {
            const int ap = 16 * w + g + 8 * h;
            uint8_t* dst = sX[q] + ap * 64 + ((t ^ ((ap >> 1) & 3)) << 4);
            *reinterpret_cast<uint4*>(dst) = make_uint4(pr[h][0], pr[h][1], pr[h][2], pr[h][3]);
            *reinterpret_cast<uint4*>(dst + 4096) = make_uint4(pi[h][0], pi[h][1], pi[h][2], pi[h][3]);
        }
    }
    fence_async_smem();
    if (q) named_bar(2, 128); else named_bar(1, 128);
    wg_fence();
#pragma unroll
    for (int ks = 0; ks < 4; ks++) {
        const uint64_t dr = mk_desc(xa + ks * 1024, 16, 512, 2), di = mk_desc(xa + 4096 + ks * 1024, 16, 512, 2);
        wg_n32_b<1, 1>(yr, fc[ks], dr, ks);
        wg_n32_b<1, 1>(yi, fs[ks], dr, ks);
        wg_n32_b<-1, 1>(yr, fs[ks], di, 1);
        wg_n32_b<1, 1>(yi, fc[ks], di, 1);
    }
    wg_commit();
    wg_wait<0>();
#pragma unroll
    for (int h = 0; h < 2; h++) {
        const int a = 16 * w + g + 8 * h;
        uint8_t* dst = g_Z + (size_t)(2 * a + (t >> 1)) * ZSTRIDE + cidx * 64 + (((t & 1) ^ ((cidx >> 1) & 1)) << 4);
        *reinterpret_cast<uint4*>(dst) = make_uint4(pack_b2(yr[2 * h], yr[2 * h + 1]), pack_b2(yr[4 + 2 * h], yr[5 + 2 * h]),
                                                    pack_b2(yr[8 + 2 * h], yr[9 + 2 * h]), pack_b2(yr[12 + 2 * h], yr[13 + 2 * h]));
        *reinterpret_cast<uint4*>(dst + 32) = make_uint4(pack_b2(yi[2 * h], yi[2 * h + 1]), pack_b2(yi[4 + 2 * h], yi[5 + 2 * h]),
                                                         pack_b2(yi[8 + 2 * h], yi[9 + 2 * h]), pack_b2(yi[12 + 2 * h], yi[13 + 2 * h]));
    }
}

__global__ void __launch_bounds__(256) k3_rowidft(const __nv_bfloat16* __restrict__ x) {
    __shared__ __align__(1024) uint8_t sZ[16384];
    __shared__ float sred[8][32];
    __shared__ __align__(8) uint64_t sbar;
    const int tid = threadIdx.x, warp = tid >> 5, lane = tid & 31, g = lane >> 2, t = lane & 3, cta = blockIdx.x;
    const int r = 8 * warp + g;
    pdl_trigger();
    if (tid == 0) {
        mbar_init(s2u(&sbar), 1);
        fence_mbar_init();
    }
    if (tid < 124) *reinterpret_cast<uint4*>(sZ + 14400 + tid * 16) = make_uint4(0, 0, 0, 0);
    float xv[4][7];
    {
        const unsigned short* xp = reinterpret_cast<const unsigned short*>(x) + (size_t)(cta * 16 + 2 * t) * D_ + r;
#pragma unroll
        for (int i = 0; i < 4; i++)
#pragma unroll
            for (int m = 0; m < 7; m++) xv[i][m] = __uint_as_float((uint32_t)__ldg(xp + ((i >> 1) * 8 + (i & 1)) * D_ + 64 * m) << 16);
    }
    uint32_t af[8][4];
#pragma unroll
    for (int ks = 0; ks < 8; ks++)
#pragma unroll
        for (int hh = 0; hh < 2; hh++) {
            float c, s;
            cs2pi(((8 * ks + 4 * hh + t) * r) & 63, 64, c, s);
            const float sg = (ks >= 4) ? -0.125f : 0.125f;
            af[ks][2 * hh] = pack_b2(c * 0.125f, -s * sg);
            af[ks][2 * hh + 1] = pack_b2(s * 0.125f, c * sg);
        }
    float twc[3], tws[3];
#pragma unroll
    for (int b = 0; b < 3; b++) {
        cs2pi(r * (b + 1), 448, twc[b], tws[b]);
        twc[b] *= (1.f / 7.f);
        tws[b] *= (1.f / 7.f);
    }
    float xs[4];
#pragma unroll
    for (int i = 0; i < 4; i++) xs[i] = ((xv[i][0] + xv[i][1]) + (xv[i][2] + xv[i][3])) + ((xv[i][4] + xv[i][5]) + xv[i][6]);
    fence_async_smem();
    __syncthreads();
    pdl_wait();
    const uint32_t za = s2u(sZ), bar = s2u(&sbar);
    if (tid == 0) {
        mbar_expect(bar, 14400);
        bulk_g2s(za, g_Z + (size_t)cta * ZSTRIDE, 14400, bar);
    }
    mbar_wait(bar, 0);
    float acc[32];
    wg_fence();
#pragma unroll
    for (int ks = 0; ks < 8; ks++) wg_n64_b<1>(acc, af[ks], mk_desc(za + ks * 512, 4096, 256, 3), ks);
    wg_commit();
    wg_wait<0>();
    float st[8];
#pragma unroll
    for (int i = 0; i < 4; i++) {
        const int o = (i >> 1) * 4 + (i & 1);
        const float u0r = acc[24 + o];
        const float u0 = u0r * (1.f / 7.f);
        float pr[3], pi[3];
#pragma unroll
        for (int b = 0; b < 3; b++) {
            const float ur = acc[8 * b + o], ui = acc[8 * b + o + 2];
            pr[b] = fmaf(ur, twc[b], -ui * tws[b]);
            pi[b] = fmaf(ui, twc[b], ur * tws[b]);
        }
        const float e1 = fmaf(C3, pr[2], fmaf(C2, pr[1], fmaf(C1, pr[0], u0)));
        const float e2 = fmaf(C1, pr[2], fmaf(C3, pr[1], fmaf(C2, pr[0], u0)));
        const float e3 = fmaf(C2, pr[2], fmaf(C1, pr[1], fmaf(C3, pr[0], u0)));
        const float o1 = fmaf(S3, pi[2], fmaf(S2, pi[1], S1 * pi[0]));
        const float o2 = fmaf(-S1, pi[2], fmaf(-S3, pi[1], S2 * pi[0]));
        const float o3 = fmaf(S2, pi[2], fmaf(-S1, pi[1], S3 * pi[0]));
        xv[i][0] += (u0 + pr[0]) + (pr[1] + pr[2]);
        xv[i][1] += e1 - o1;
        xv[i][6] += e1 + o1;
        xv[i][2] += e2 - o2;
        xv[i][5] += e2 + o2;
        xv[i][3] += e3 - o3;
        xv[i][4] += e3 + o3;
        float ss = 0.f;
#pragma unroll
        for (int m = 0; m < 7; m++) ss = fmaf(xv[i][m], xv[i][m], ss);
        st[i] = xs[i] + u0r;
        st[4 + i] = ss;
    }
    {
        const bool b2 = lane & 16, b1 = lane & 8, b0 = lane & 4;
#pragma unroll
        for (int i = 0; i < 4; i++) {
            const float snd = b2 ? st[i] : st[i + 4], keep = b2 ? st[i + 4] : st[i];
            st[i] = keep + __shfl_xor_sync(0xffffffffu, snd, 16);
        }
#pragma unroll
        for (int i = 0; i < 2; i++) {
            const float snd = b1 ? st[i] : st[i + 2], keep = b1 ? st[i + 2] : st[i];
            st[i] = keep + __shfl_xor_sync(0xffffffffu, snd, 8);
        }
        const float snd = b0 ? st[0] : st[1], keep = b0 ? st[1] : st[0];
        sred[warp][lane] = keep + __shfl_xor_sync(0xffffffffu, snd, 4);
    }
    __syncthreads();
    float tot = 0.f;
#pragma unroll
    for (int i = 0; i < 8; i++) tot += sred[i][lane];
    const float other = __shfl_xor_sync(0xffffffffu, tot, 16);
    const float sm = (lane & 16) ? other : tot, sq = (lane & 16) ? tot : other;
    const float mean = sm * (1.f / 448.f);
    const float var = fmaxf(fmaf(-mean, mean, sq * (1.f / 448.f)), 0.f);
    const float r1 = rsqrtf(var + 1e-5f);
    const float sc = r1 * rsqrtf(fmaf(var * r1, r1, 1e-5f));
    const float mo = -mean * sc;
    float scl[4], off[4];
#pragma unroll
    for (int i = 0; i < 4; i++) {
        scl[i] = __shfl_sync(0xffffffffu, sc, 4 * i + t);
        off[i] = __shfl_sync(0xffffffffu, mo, 4 * i + t);
    }
#pragma unroll
    for (int m = 0; m < 7; m++) {
        const int d = 64 * m + r, dt = d / 112, dl = d - dt * 112;
#pragma unroll
        for (int rg = 0; rg < 2; rg++) {
            const size_t o = ((size_t)(dt * 256 + cta * 2 + rg) * 112 + dl) * 16 + t * 4;
            *reinterpret_cast<uint32_t*>(g_hn + o) =
                pack_b2(fmaf(xv[2 * rg][m], scl[2 * rg], off[2 * rg]), fmaf(xv[2 * rg + 1][m], scl[2 * rg + 1], off[2 * rg + 1]));
        }
    }
#pragma unroll
    for (int m = 0; m < 7; m++) {
        const int d = 64 * m + r, dt = d / 112, dl = d - dt * 112;
#pragma unroll
        for (int rg = 0; rg < 2; rg++) {
            const size_t o = ((size_t)(dt * 256 + cta * 2 + rg) * 112 + dl) * 16 + t * 4;
            *reinterpret_cast<uint32_t*>(g_h + o) = pack_b2(xv[2 * rg][m], xv[2 * rg + 1][m]);
        }
    }
}

constexpr int WS = 7, AS = 4;
constexpr int SM_W = 0, SM_A = WS * 16384, SM_X = SM_A + AS * 14336, SM_BAR = SM_X + 28672, SM_TOTAL = SM_BAR + 256 + 1024;

template <int MODE>
__global__ void __cluster_dims__(2, 1, 1) __launch_bounds__(320)
    gemm_kernel(const __grid_constant__ CUtensorMap tmw, const __nv_bfloat16* __restrict__ bias, __nv_bfloat16* __restrict__ out) {
    constexpr int KB = MODE ? 14 : 16;
    extern __shared__ uint8_t smem_raw[];
    const uint32_t sb = (s2u(smem_raw) + 1023) & ~1023u;
    const int tid = threadIdx.x, warp = tid >> 5, lane = tid & 31;
    const int kh = blockIdx.x & 1, dt = (blockIdx.x >> 1) & 3, mt = blockIdx.x >> 3;
    const uint32_t wfull = sb + SM_BAR, wempty = wfull + 8 * WS, afull = wempty + 8 * WS, aempty = afull + 8 * AS, xbar = aempty + 8 * AS;
    if (MODE == 0) pdl_trigger();
    if (tid == 0) {
        for (int i = 0; i < WS; i++) { mbar_init(wfull + 8 * i, 1); mbar_init(wempty + 8 * i, 8); }
        for (int i = 0; i < AS; i++) { mbar_init(afull + 8 * i, 1); mbar_init(aempty + 8 * i, 8); }
        for (int i = 0; i < 8; i++) { mbar_init(xbar + 8 * i, 1); mbar_expect(xbar + 8 * i, 3584); }
        fence_mbar_init();
    }
    __syncthreads();
    asm volatile("barrier.cluster.arrive.release.aligned;" ::: "memory");
    if (warp == 8) {
        if (lane == 0) {
            int st = 0, ph = 1;
            for (int kb = 0; kb < KB; kb++) {
                mbar_wait(wempty + 8 * st, ph);
                mbar_expect(wfull + 8 * st, 16384);
                tma_3d(sb + SM_W + st * 16384, &tmw, 0, (kh * KB + kb) * 64, mt * 2, wfull + 8 * st);
                if (++st == WS) { st = 0; ph ^= 1; }
            }
        }
        __syncwarp();
        asm volatile("barrier.cluster.wait.acquire.aligned;" ::: "memory");
    } else if (warp == 9) {
        if (lane == 0) {
            pdl_wait();
            asm volatile("fence.proxy.async.global;" ::: "memory");
            const uint8_t* src = (MODE ? g_g + (size_t)(dt * 28 + kh * KB) * 14336 : g_hn + (size_t)(dt * 32 + kh * KB) * 14336);
            int st = 0, ph = 1;
            for (int kb = 0; kb < KB; kb++) {
                mbar_wait(aempty + 8 * st, ph);
                mbar_expect(afull + 8 * st, 14336);
                bulk_g2s(sb + SM_A + st * 14336, src + (size_t)kb * 14336, 14336, afull + 8 * st);
                if (++st == AS) { st = 0; ph ^= 1; }
            }
        }
        __syncwarp();
        asm volatile("barrier.cluster.wait.acquire.aligned;" ::: "memory");
    } else {
        const int wg = warp >> 2, g = lane >> 2, t = lane & 3;
        const int mrow = mt * 128 + warp * 16 + 8 * kh + g;
        const float bv = __bfloat162float(bias[mrow]);
        uint32_t hres[14];
        if (MODE == 1) {
            pdl_wait();
            const unsigned short* hp = reinterpret_cast<const unsigned short*>(g_h + ((size_t)(dt * 256 + (mrow >> 3)) * 112 + 2 * t) * 16) + g;
#pragma unroll
            for (int j = 0; j < 14; j++) {
                const uint32_t lo = __ldcg(hp + j * 64), hi = __ldcg(hp + j * 64 + 8);
                hres[j] = lo | (hi << 16);
            }
        }
        float acc[56];
        int ws = 0, wph = 0, as = 0, aph = 0, pws = 0, pas = 0;
#pragma unroll 1
        for (int kb = 0; kb < KB; kb++) {
            mbar_wait(wfull + 8 * ws, wph);
            mbar_wait(afull + 8 * as, aph);
            const uint32_t wa = sb + SM_W + ws * 16384 + wg * 8192, aa = sb + SM_A + as * 14336;
            wg_fence();
#pragma unroll
            for (int ks = 0; ks < 4; ks++) {
                const uint64_t da = mk_desc(wa + ks * 2048, 16, 1024, 1);
                const uint64_t db = MODE ? mk_desc(aa + ks * 256, 128, 1024, 0) : mk_desc(aa + ks * 3584, 1792, 128, 0);
                wg_n112_ss<MODE>(acc, da, db, kb | ks);
            }
            wg_commit();
            if (kb > 0) {
                wg_wait<1>();
                if (lane == 0) { mbar_arrive(wempty + 8 * pws); mbar_arrive(aempty + 8 * pas); }
            }
            pws = ws; pas = as;
            if (++ws == WS) { ws = 0; wph ^= 1; }
            if (++as == AS) { as = 0; aph ^= 1; }
        }
        wg_wait<0>();
        asm volatile("barrier.cluster.wait.acquire.aligned;" ::: "memory");
        const uint32_t xloc = sb + SM_X + warp * 3584 + lane * 16;
        {
            uint32_t xrem, brem;
            asm volatile("mapa.shared::cluster.u32 %0, %1, %2;" : "=r"(xrem) : "r"(xloc), "r"(kh ^ 1));
            asm volatile("mapa.shared::cluster.u32 %0, %1, %2;" : "=r"(brem) : "r"(xbar + 8 * warp), "r"(kh ^ 1));
#pragma unroll
            for (int i = 0; i < 7; i++) {
                const float v0 = kh ? acc[8 * i] : acc[8 * i + 2], v1 = kh ? acc[8 * i + 1] : acc[8 * i + 3];
                const float v2 = kh ? acc[8 * i + 4] : acc[8 * i + 6], v3 = kh ? acc[8 * i + 5] : acc[8 * i + 7];
                asm volatile("st.async.weak.shared::cluster.mbarrier::complete_tx::bytes.v4.f32 [%0], {%1,%2,%3,%4}, [%5];" ::"r"(xrem + i * 512), "f"(v0),
                             "f"(v1), "f"(v2), "f"(v3), "r"(brem)
                             : "memory");
            }
        }
        mbar_wait_cluster(xbar + 8 * warp, 0);
        uint32_t res[14];
#pragma unroll
        for (int i = 0; i < 7; i++) {
            float p0, p1, p2, p3;
            asm volatile("ld.shared.v4.f32 {%0,%1,%2,%3}, [%4];" : "=f"(p0), "=f"(p1), "=f"(p2), "=f"(p3) : "r"(xloc + i * 512) : "memory");
            float v[4];
            v[0] = (kh ? acc[8 * i + 2] : acc[8 * i]) + p0 + bv;
            v[1] = (kh ? acc[8 * i + 3] : acc[8 * i + 1]) + p1 + bv;
            v[2] = (kh ? acc[8 * i + 6] : acc[8 * i + 4]) + p2 + bv;
            v[3] = (kh ? acc[8 * i + 7] : acc[8 * i + 5]) + p3 + bv;
            if (MODE == 0) {
#pragma unroll
                for (int e = 0; e < 4; e++) {
                    const float u = v[e];
                    const float z = u * fmaf(u * u, -0.1029432397f, -2.302208198f);
                    v[e] = __fdividef(u, 1.f + exp2f(z));
                }
            } else {
                v[0] += bf_lo(hres[2 * i]); v[1] += bf_hi(hres[2 * i]);
                v[2] += bf_lo(hres[2 * i + 1]); v[3] += bf_hi(hres[2 * i + 1]);
            }
            res[2 * i] = pack_b2(v[0], v[1]);
            res[2 * i + 1] = pack_b2(v[2], v[3]);
        }
        if (MODE == 0) {
            uint8_t* dst = g_g + (size_t)(dt * 28 + (mrow >> 6)) * 14336 + (mrow & 63) * 16 + t * 4;
#pragma unroll
            for (int j = 0; j < 14; j++) *reinterpret_cast<uint32_t*>(dst + j * 1024) = res[j];
        } else {
            __syncwarp();
            const uint32_t stg = sb + SM_X + warp * 3584;
#pragma unroll
            for (int j = 0; j < 14; j++) asm volatile("st.shared.b32 [%0], %1;" ::"r"(stg + g * 240 + j * 16 + t * 4), "r"(res[j]) : "memory");
            __syncwarp();
            uint8_t* ob = reinterpret_cast<uint8_t*>(out) + (size_t)(mt * 128 + warp * 16 + 8 * kh) * 896 + dt * 224;
#pragma unroll
            for (int i = 0; i < 4; i++) {
                const int c = i * 32 + lane, row = c / 14, ch = c - row * 14;
                if (c < 112) {
                    uint4 v;
                    asm volatile("ld.shared.v4.b32 {%0,%1,%2,%3}, [%4];" : "=r"(v.x), "=r"(v.y), "=r"(v.z), "=r"(v.w) : "r"(stg + row * 240 + ch * 16) : "memory");
                    *reinterpret_cast<uint4*>(ob + row * 896 + ch * 16) = v;
                }
            }
        }
    }
}

typedef CUresult (*EncodeFn)(CUtensorMap*, CUtensorMapDataType, cuuint32_t, void*, const cuuint64_t*, const cuuint64_t*, const cuuint32_t*,
                             const cuuint32_t*, CUtensorMapInterleave, CUtensorMapSwizzle, CUtensorMapL2promotion, CUtensorMapFloatOOBfill);

void make_wmap(EncodeFn enc, CUtensorMap* tm, const void* ptr, int K, int M) {
    cuuint64_t dims[3] = {64, (cuuint64_t)K, (cuuint64_t)(M / 64)};
    cuuint64_t strides[2] = {(cuuint64_t)M * 2, 128};
    cuuint32_t box[3] = {64, 64, 2};
    cuuint32_t es[3] = {1, 1, 1};
    enc(tm, CU_TENSOR_MAP_DATA_TYPE_BFLOAT16, 3, const_cast<void*>(ptr), dims, strides, box, es, CU_TENSOR_MAP_INTERLEAVE_NONE,
        CU_TENSOR_MAP_SWIZZLE_128B, CU_TENSOR_MAP_L2_PROMOTION_L2_256B, CU_TENSOR_MAP_FLOAT_OOB_FILL_NONE);
}

template <typename... KArgs, typename... Args>
void launch(void (*kern)(KArgs...), int grid, int block, int smem, bool pdl, Args... args) {
    cudaLaunchConfig_t cfg = {};
    cfg.gridDim = dim3(grid);
    cfg.blockDim = dim3(block);
    cfg.dynamicSmemBytes = smem;
    cfg.stream = cudaStreamPerThread;
    cudaLaunchAttribute at[1];
    at[0].id = cudaLaunchAttributeProgrammaticStreamSerialization;
    at[0].val.programmaticStreamSerializationAllowed = 1;
    cfg.attrs = at;
    cfg.numAttrs = pdl ? 1 : 0;
    cudaLaunchKernelEx(&cfg, kern, KArgs(args)...);
}

}

extern "C" void kernel_launch(void* const* d_in, const int* in_sizes, int n_in, void* d_out, int out_size) {
    const __nv_bfloat16* x = (const __nv_bfloat16*)d_in[0];
    const __nv_bfloat16* wr = (const __nv_bfloat16*)d_in[1];
    const __nv_bfloat16* wi = (const __nv_bfloat16*)d_in[2];
    const __nv_bfloat16* w1 = (const __nv_bfloat16*)d_in[4];
    const __nv_bfloat16* b1 = (const __nv_bfloat16*)d_in[5];
    const __nv_bfloat16* w2 = (const __nv_bfloat16*)d_in[6];
    const __nv_bfloat16* b2 = (const __nv_bfloat16*)d_in[7];
    __nv_bfloat16* out = (__nv_bfloat16*)d_out;

    static EncodeFn enc = nullptr;
    if (!enc) {
        void* fn = nullptr;
        cudaDriverEntryPointQueryResult qr;
        cudaGetDriverEntryPoint("cuTensorMapEncodeTiled", &fn, cudaEnableDefault, &qr);
        enc = (EncodeFn)fn;
        cudaFuncSetAttribute(k2_col, cudaFuncAttributeMaxDynamicSharedMemorySize, 49168);
        cudaFuncSetAttribute(gemm_kernel<0>, cudaFuncAttributeMaxDynamicSharedMemorySize, SM_TOTAL);
        cudaFuncSetAttribute(gemm_kernel<1>, cudaFuncAttributeMaxDynamicSharedMemorySize, SM_TOTAL);
    }
    CUtensorMap tm1, tm2;
    make_wmap(enc, &tm1, w1, S_, F_);
    make_wmap(enc, &tm2, w2, F_, S_);

    launch(k1_rowdft, 128, 384, 0, false, x, wr, wi, w1, w2);
    launch(k2_col, 113, 256, 49168, true);
    launch(k3_rowidft, 128, 256, 0, true, x);
    launch(gemm_kernel<0>, 112, 320, SM_TOTAL, true, tm1, b1, out);
    launch(gemm_kernel<1>, 128, 320, SM_TOTAL, true, tm2, b2, out);
}
```

```cpp
#include <cuda_runtime.h>
#include <cuda_bf16.h>
#include <cuda_fp16.h>
#include <cuda.h>
#include <stdint.h>

namespace {

constexpr int S_ = 2048, D_ = 448, F_ = 1792, DF_ = 225;
constexpr int ZSTRIDE = 16384;
constexpr int NCTA = 128;

constexpr int TOFF_G = 0;
constexpr int TOFF_A2 = 4096;
constexpr int TOFF_TW2 = 8192;
constexpr int TOFF_A4 = 12288;
constexpr int TOFF_A3 = 16384;
constexpr int TOFF_TW3 = 20480;
constexpr int TAB_WORDS = 20864;
__device__ __align__(1024) const uint32_t g_tab[TAB_WORDS] = {
0x3c003c00,0x3c003c00,0x3c003c00,0x3c003c00,0x3c003c00,0x3c003c00,0x3c003c00,0x3c003c00,0x3c003c00,0x3c003c00,0x3c003c00,0x3c003c00,0x3c003c00,0x3c003c00,0x3c003c00,0x3c003c00,
0,0,0,0,0,0,0,0,0,0,0,0,0,0,0,0,
0xb23e0000,0xb872b61f,0xbaa7b9a8,0xbbd9bb64,0x3bd93c00,0x3aa73b64,0x387239a8,0x323e361f,0x323e0000,0x3872361f,0x3aa739a8,0x3bd93b64,0xbbd9bc00,0xbaa7bb64,0xb872b9a8,0xb23eb61f,
0x3bd93c00,0x3aa73b64,0x387239a8,0x323e361f,0x323e0000,0x3872361f,0x3aa739a8,0x3bd93b64,0xbbd9bc00,0xbaa7bb64,0xb872b9a8,0xb23eb61f,0xb23e0000,0xb872b61f,0xbaa7b9a8,0xbbd9bb64,
0x3b643c00,0x361f39a8,0xb61f0000,0xbb64b9a8,0xbb64bc00,0xb61fb9a8,0x361f0000,0x3b6439a8,0x3b643c00,0x361f39a8,0xb61f0000,0xbb64b9a8,0xbb64bc00,0xb61fb9a8,0x361f0000,0x3b6439a8,
0x361f0000,0x3b6439a8,0x3b643c00,0x361f39a8,0xb61f0000,0xbb64b9a8,0xbb64bc00,0xb61fb9a8,0x361f0000,0x3b6439a8,0x3b643c00,0x361f39a8,0xb61f0000,0xbb64b9a8,0xbb64bc00,0xb61fb9a8,
0xb8720000,0xbbd9bb64,0xb23eb9a8,0x3aa7361f,0xbaa7bc00,0x323eb61f,0x3bd939a8,0x38723b64,0x38720000,0x3bd93b64,0x323e39a8,0xbaa7b61f,0x3aa73c00,0xb23e361f,0xbbd9b9a8,0xb872bb64,
0x3aa73c00,0xb23e361f,0xbbd9b9a8,0xb872bb64,0xb8720000,0xbbd9bb64,0xb23eb9a8,0x3aa7361f,0xbaa7bc00,0x323eb61f,0x3bd939a8,0x38723b64,0x38720000,0x3bd93b64,0x323e39a8,0xbaa7b61f,
0x39a80000,0x39a83c00,0xb9a80000,0xb9a8bc00,0x39a80000,0x39a83c00,0xb9a80000,0xb9a8bc00,0x39a80000,0x39a83c00,0xb9a80000,0xb9a8bc00,0x39a80000,0x39a83c00,0xb9a80000,0xb9a8bc00,
0x39a83c00,0xb9a80000,0xb9a8bc00,0x39a80000,0x39a83c00,0xb9a80000,0xb9a8bc00,0x39a80000,0x39a83c00,0xb9a80000,0xb9a8bc00,0x39a80000,0x39a83c00,0xb9a80000,0xb9a8bc00,0x39a80000,
0x38723c00,0xbbd9b61f,0x323eb9a8,0x3aa73b64,0x3aa70000,0x323e3b64,0xbbd9b9a8,0x3872b61f,0xb872bc00,0x3bd9361f,0xb23e39a8,0xbaa7bb64,0xbaa70000,0xb23ebb64,0x3bd939a8,0xb872361f,
0xbaa70000,0xb23ebb64,0x3bd939a8,0xb872361f,0x38723c00,0xbbd9b61f,0x323eb9a8,0x3aa73b64,0x3aa70000,0x323e3b64,0xbbd9b9a8,0x3872b61f,0xb872bc00,0x3bd9361f,0xb23e39a8,0xbaa7bb64,
0x3b640000,0xb61f39a8,0xb61fbc00,0x3b6439a8,0xbb640000,0x361fb9a8,0x361f3c00,0xbb64b9a8,0x3b640000,0xb61f39a8,0xb61fbc00,0x3b6439a8,0xbb640000,0x361fb9a8,0x361f3c00,0xbb64b9a8,
0x361f3c00,0xbb64b9a8,0x3b640000,0xb61f39a8,0xb61fbc00,0x3b6439a8,0xbb640000,0x361fb9a8,0x361f3c00,0xbb64b9a8,0x3b640000,0xb61f39a8,0xb61fbc00,0x3b6439a8,0xbb640000,0x361fb9a8,
0x323e3c00,0xb872bb64,0x3aa739a8,0xbbd9b61f,0xbbd90000,0x3aa7b61f,0xb87239a8,0x323ebb64,0xb23ebc00,0x38723b64,0xbaa7b9a8,0x3bd9361f,0x3bd90000,0xbaa7361f,0x3872b9a8,0xb23e3b64,
0xbbd90000,0x3aa7b61f,0xb87239a8,0x323ebb64,0xb23ebc00,0x38723b64,0xbaa7b9a8,0x3bd9361f,0x3bd90000,0xbaa7361f,0x3872b9a8,0xb23e3b64,0x323e3c00,0xb872bb64,0x3aa739a8,0xbbd9b61f,
0x3c00,0xbc00,0x3c00,0xbc00,0x3c00,0xbc00,0x3c00,0xbc00,0x3c00,0xbc00,0x3c00,0xbc00,0x3c00,0xbc00,0x3c00,0xbc00,
0x3c000000,0xbc000000,0x3c000000,0xbc000000,0x3c000000,0xbc000000,0x3c000000,0xbc000000,0x3c000000,0xbc000000,0x3c000000,0xbc000000,0x3c000000,0xbc000000,0x3c000000,0xbc000000,
0xbbd90000,0x3aa7361f,0xb872b9a8,0x323e3b64,0xb23e3c00,0x3872bb64,0xbaa739a8,0x3bd9b61f,0x3bd90000,0xbaa7b61f,0x387239a8,0xb23ebb64,0x323ebc00,0xb8723b64,0x3aa7b9a8,0xbbd9361f,
0xb23e3c00,0x3872bb64,0xbaa739a8,0x3bd9b61f,0x3bd90000,0xbaa7b61f,0x387239a8,0xb23ebb64,0x323ebc00,0xb8723b64,0x3aa7b9a8,0xbbd9361f,0xbbd90000,0x3aa7361f,0xb872b9a8,0x323e3b64,
0xb61f3c00,0x3b64b9a8,0xbb640000,0x361f39a8,0x361fbc00,0xbb6439a8,0x3b640000,0xb61fb9a8,0xb61f3c00,0x3b64b9a8,0xbb640000,0x361f39a8,0x361fbc00,0xbb6439a8,0x3b640000,0xb61fb9a8,
0x3b640000,0xb61fb9a8,0xb61f3c00,0x3b64b9a8,0xbb640000,0x361f39a8,0x361fbc00,0xbb6439a8,0x3b640000,0xb61fb9a8,0xb61f3c00,0x3b64b9a8,0xbb640000,0x361f39a8,0x361fbc00,0xbb6439a8,
0xbaa70000,0xb23e3b64,0x3bd9b9a8,0xb872b61f,0x3872bc00,0xbbd9361f,0x323e39a8,0x3aa7bb64,0x3aa70000,0x323ebb64,0xbbd939a8,0x3872361f,0xb8723c00,0x3bd9b61f,0xb23eb9a8,0xbaa73b64,
0xb8723c00,0x3bd9b61f,0xb23eb9a8,0xbaa73b64,0xbaa70000,0xb23e3b64,0x3bd9b9a8,0xb872b61f,0x3872bc00,0xbbd9361f,0x323e39a8,0x3aa7bb64,0x3aa70000,0x323ebb64,0xbbd939a8,0x3872361f,
0x39a80000,0x39a8bc00,0xb9a80000,0xb9a83c00,0x39a80000,0x39a8bc00,0xb9a80000,0xb9a83c00,0x39a80000,0x39a8bc00,0xb9a80000,0xb9a83c00,0x39a80000,0x39a8bc00,0xb9a80000,0xb9a83c00,
0xb9a83c00,0x39a80000,0x39a8bc00,0xb9a80000,0xb9a83c00,0x39a80000,0x39a8bc00,0xb9a80000,0xb9a83c00,0x39a80000,0x39a8bc00,0xb9a80000,0xb9a83c00,0x39a80000,0x39a8bc00,0xb9a80000,
0xbaa73c00,0x323e361f,0x3bd9b9a8,0x3872bb64,0x38720000,0x3bd9bb64,0x323eb9a8,0xbaa7361f,0x3aa7bc00,0xb23eb61f,0xbbd939a8,0xb8723b64,0xb8720000,0xbbd93b64,0xb23e39a8,0x3aa7b61f,
0xb8720000,0xbbd93b64,0xb23e39a8,0x3aa7b61f,0xbaa73c00,0x323e361f,0x3bd9b9a8,0x3872bb64,0x38720000,0x3bd9bb64,0x323eb9a8,0xbaa7361f,0x3aa7bc00,0xb23eb61f,0xbbd939a8,0xb8723b64,
0x361f0000,0x3b64b9a8,0x3b64bc00,0x361fb9a8,0xb61f0000,0xbb6439a8,0xbb643c00,0xb61f39a8,0x361f0000,0x3b64b9a8,0x3b64bc00,0x361fb9a8,0xb61f0000,0xbb6439a8,0xbb643c00,0xb61f39a8,
0xbb643c00,0xb61f39a8,0x361f0000,0x3b64b9a8,0x3b64bc00,0x361fb9a8,0xb61f0000,0xbb6439a8,0xbb643c00,0xb61f39a8,0x361f0000,0x3b64b9a8,0x3b64bc00,0x361fb9a8,0xb61f0000,0xbb6439a8,
0xbbd93c00,0xbaa73b64,0xb87239a8,0xb23e361f,0xb23e0000,0xb872361f,0xbaa739a8,0xbbd93b64,0x3bd9bc00,0x3aa7bb64,0x3872b9a8,0x323eb61f,0x323e0000,0x3872b61f,0x3aa7b9a8,0x3bd9bb64,
0xb23e0000,0xb872361f,0xbaa739a8,0xbbd93b64,0x3bd9bc00,0x3aa7bb64,0x3872b9a8,0x323eb61f,0x323e0000,0x3872b61f,0x3aa7b9a8,0x3bd9bb64,0xbbd93c00,0xbaa73b64,0xb87239a8,0xb23e361f,
0xbc003c00,0xbc003c00,0xbc003c00,0xbc003c00,0xbc003c00,0xbc003c00,0xbc003c00,0xbc003c00,0xbc003c00,0xbc003c00,0xbc003c00,0xbc003c00,0xbc003c00,0xbc003c00,0xbc003c00,0xbc003c00,
0,0,0,0,0,0,0,0,0,0,0,0,0,0,0,0,
0x323e0000,0x3872b61f,0x3aa7b9a8,0x3bd9bb64,0xbbd93c00,0xbaa73b64,0xb87239a8,0xb23e361f,0xb23e0000,0xb872361f,0xbaa739a8,0xbbd93b64,0x3bd9bc00,0x3aa7bb64,0x3872b9a8,0x323eb61f,
0xbbd93c00,0xbaa73b64,0xb87239a8,0xb23e361f,0xb23e0000,0xb872361f,0xbaa739a8,0xbbd93b64,0x3bd9bc00,0x3aa7bb64,0x3872b9a8,0x323eb61f,0x323e0000,0x3872b61f,0x3aa7b9a8,0x3bd9bb64,
0xbb643c00,0xb61f39a8,0x361f0000,0x3b64b9a8,0x3b64bc00,0x361fb9a8,0xb61f0000,0xbb6439a8,0xbb643c00,0xb61f39a8,0x361f0000,0x3b64b9a8,0x3b64bc00,0x361fb9a8,0xb61f0000,0xbb6439a8,
0xb61f0000,0xbb6439a8,0xbb643c00,0xb61f39a8,0x361f0000,0x3b64b9a8,0x3b64bc00,0x361fb9a8,0xb61f0000,0xbb6439a8,0xbb643c00,0xb61f39a8,0x361f0000,0x3b64b9a8,0x3b64bc00,0x361fb9a8,
0x38720000,0x3bd9bb64,0x323eb9a8,0xbaa7361f,0x3aa7bc00,0xb23eb61f,0xbbd939a8,0xb8723b64,0xb8720000,0xbbd93b64,0xb23e39a8,0x3aa7b61f,0xbaa73c00,0x323e361f,0x3bd9b9a8,0x3872bb64,
0xbaa73c00,0x323e361f,0x3bd9b9a8,0x3872bb64,0x38720000,0x3bd9bb64,0x323eb9a8,0xbaa7361f,0x3aa7bc00,0xb23eb61f,0xbbd939a8,0xb8723b64,0xb8720000,0xbbd93b64,0xb23e39a8,0x3aa7b61f,
0xb9a80000,0xb9a83c00,0x39a80000,0x39a8bc00,0xb9a80000,0xb9a83c00,0x39a80000,0x39a8bc00,0xb9a80000,0xb9a83c00,0x39a80000,0x39a8bc00,0xb9a80000,0xb9a83c00,0x39a80000,0x39a8bc00,
0xb9a83c00,0x39a80000,0x39a8bc00,0xb9a80000,0xb9a83c00,0x39a80000,0x39a8bc00,0xb9a80000,0xb9a83c00,0x39a80000,0x39a8bc00,0xb9a80000,0xb9a83c00,0x39a80000,0x39a8bc00,0xb9a80000,
0xb8723c00,0x3bd9b61f,0xb23eb9a8,0xbaa73b64,0xbaa70000,0xb23e3b64,0x3bd9b9a8,0xb872b61f,0x3872bc00,0xbbd9361f,0x323e39a8,0x3aa7bb64,0x3aa70000,0x323ebb64,0xbbd939a8,0x3872361f,
0x3aa70000,0x323ebb64,0xbbd939a8,0x3872361f,0xb8723c00,0x3bd9b61f,0xb23eb9a8,0xbaa73b64,0xbaa70000,0xb23e3b64,0x3bd9b9a8,0xb872b61f,0x3872bc00,0xbbd9361f,0x323e39a8,0x3aa7bb64,
0xbb640000,0x361f39a8,0x361fbc00,0xbb6439a8,0x3b640000,0xb61fb9a8,0xb61f3c00,0x3b64b9a8,0xbb640000,0x361f39a8,0x361fbc00,0xbb6439a8,0x3b640000,0xb61fb9a8,0xb61f3c00,0x3b64b9a8,
0xb61f3c00,0x3b64b9a8,0xbb640000,0x361f39a8,0x361fbc00,0xbb6439a8,0x3b640000,0xb61fb9a8,0xb61f3c00,0x3b64b9a8,0xbb640000,0x361f39a8,0x361fbc00,0xbb6439a8,0x3b640000,0xb61fb9a8,
0xb23e3c00,0x3872bb64,0xbaa739a8,0x3bd9b61f,0x3bd90000,0xbaa7b61f,0x387239a8,0xb23ebb64,0x323ebc00,0xb8723b64,0x3aa7b9a8,0xbbd9361f,0xbbd90000,0x3aa7361f,0xb872b9a8,0x323e3b64,
0x3bd90000,0xbaa7b61f,0x387239a8,0xb23ebb64,0x323ebc00,0xb8723b64,0x3aa7b9a8,0xbbd9361f,0xbbd90000,0x3aa7361f,0xb872b9a8,0x323e3b64,0xb23e3c00,0x3872bb64,0xbaa739a8,0x3bd9b61f,
0x3c00,0xbc00,0x3c00,0xbc00,0x3c00,0xbc00,0x3c00,0xbc00,0x3c00,0xbc00,0x3c00,0xbc00,0x3c00,0xbc00,0x3c00,0xbc00,
0xbc000000,0x3c000000,0xbc000000,0x3c000000,0xbc000000,0x3c000000,0xbc000000,0x3c000000,0xbc000000,0x3c000000,0xbc000000,0x3c000000,0xbc000000,0x3c000000,0xbc000000,0x3c000000,
0x3bd90000,0xbaa7361f,0x3872b9a8,0xb23e3b64,0x323e3c00,0xb872bb64,0x3aa739a8,0xbbd9b61f,0xbbd90000,0x3aa7b61f,0xb87239a8,0x323ebb64,0xb23ebc00,0x38723b64,0xbaa7b9a8,0x3bd9361f,
0x323e3c00,0xb872bb64,0x3aa739a8,0xbbd9b61f,0xbbd90000,0x3aa7b61f,0xb87239a8,0x323ebb64,0xb23ebc00,0x38723b64,0xbaa7b9a8,0x3bd9361f,0x3bd90000,0xbaa7361f,0x3872b9a8,0xb23e3b64,
0x361f3c00,0xbb64b9a8,0x3b640000,0xb61f39a8,0xb61fbc00,0x3b6439a8,0xbb640000,0x361fb9a8,0x361f3c00,0xbb64b9a8,0x3b640000,0xb61f39a8,0xb61fbc00,0x3b6439a8,0xbb640000,0x361fb9a8,
0xbb640000,0x361fb9a8,0x361f3c00,0xbb64b9a8,0x3b640000,0xb61f39a8,0xb61fbc00,0x3b6439a8,0xbb640000,0x361fb9a8,0x361f3c00,0xbb64b9a8,0x3b640000,0xb61f39a8,0xb61fbc00,0x3b6439a8,
0x3aa70000,0x323e3b64,0xbbd9b9a8,0x3872b61f,0xb872bc00,0x3bd9361f,0xb23e39a8,0xbaa7bb64,0xbaa70000,0xb23ebb64,0x3bd939a8,0xb872361f,0x38723c00,0xbbd9b61f,0x323eb9a8,0x3aa73b64,
0x38723c00,0xbbd9b61f,0x323eb9a8,0x3aa73b64,0x3aa70000,0x323e3b64,0xbbd9b9a8,0x3872b61f,0xb872bc00,0x3bd9361f,0xb23e39a8,0xbaa7bb64,0xbaa70000,0xb23ebb64,0x3bd939a8,0xb872361f,
0xb9a80000,0xb9a8bc00,0x39a80000,0x39a83c00,0xb9a80000,0xb9a8bc00,0x39a80000,0x39a83c00,0xb9a80000,0xb9a8bc00,0x39a80000,0x39a83c00,0xb9a80000,0xb9a8bc00,0x39a80000,0x39a83c00,
0x39a83c00,0xb9a80000,0xb9a8bc00,0x39a80000,0x39a83c00,0xb9a80000,0xb9a8bc00,0x39a80000,0x39a83c00,0xb9a80000,0xb9a8bc00,0x39a80000,0x39a83c00,0xb9a80000,0xb9a8bc00,0x39a80000,
0x3aa73c00,0xb23e361f,0xbbd9b9a8,0xb872bb64,0xb8720000,0xbbd9bb64,0xb23eb9a8,0x3aa7361f,0xbaa7bc00,0x323eb61f,0x3bd939a8,0x38723b64,0x38720000,0x3bd93b64,0x323e39a8,0xbaa7b61f,
0x38720000,0x3bd93b64,0x323e39a8,0xbaa7b61f,0x3aa73c00,0xb23e361f,0xbbd9b9a8,0xb872bb64,0xb8720000,0xbbd9bb64,0xb23eb9a8,0x3aa7361f,0xbaa7bc00,0x323eb61f,0x3bd939a8,0x38723b64,
0xb61f0000,0xbb64b9a8,0xbb64bc00,0xb61fb9a8,0x361f0000,0x3b6439a8,0x3b643c00,0x361f39a8,0xb61f0000,0xbb64b9a8,0xbb64bc00,0xb61fb9a8,0x361f0000,0x3b6439a8,0x3b643c00,0x361f39a8,
0x3b643c00,0x361f39a8,0xb61f0000,0xbb64b9a8,0xbb64bc00,0xb61fb9a8,0x361f0000,0x3b6439a8,0x3b643c00,0x361f39a8,0xb61f0000,0xbb64b9a8,0xbb64bc00,0xb61fb9a8,0x361f0000,0x3b6439a8,
0x3bd93c00,0x3aa73b64,0x387239a8,0x323e361f,0x323e0000,0x3872361f,0x3aa739a8,0x3bd93b64,0xbbd9bc00,0xbaa7bb64,0xb872b9a8,0xb23eb61f,0xb23e0000,0xb872b61f,0xbaa7b9a8,0xbbd9bb64,
0x323e0000,0x3872361f,0x3aa739a8,0x3bd93b64,0xbbd9bc00,0xbaa7bb64,0xb872b9a8,0xb23eb61f,0xb23e0000,0xb872b61f,0xbaa7b9a8,0xbbd9bb64,0x3bd93c00,0x3aa73b64,0x387239a8,0x323e361f,
0x80008000,0x80008000,0x80008000,0x80008000,0x80008000,0x80008000,0x80008000,0x80008000,0x80008000,0x80008000,0x80008000,0x80008000,0x80008000,0x80008000,0x80008000,0x80008000,
0x3c003c00,0x3c003c00,0x3c003c00,0x3c003c00,0x3c003c00,0x3c003c00,0x3c003c00,0x3c003c00,0x3c003c00,0x3c003c00,0x3c003c00,0x3c003c00,0x3c003c00,0x3c003c00,0x3c003c00,0x3c003c00,
0xbbd9bc00,0xbaa7bb64,0xb872b9a8,0xb23eb61f,0xb23e8000,0xb872b61f,0xbaa7b9a8,0xbbd9bb64,0x3bd93c00,0x3aa73b64,0x387239a8,0x323e361f,0x323e8000,0x3872361f,0x3aa739a8,0x3bd93b64,
0xb23e0000,0xb872b61f,0xbaa7b9a8,0xbbd9bb64,0x3bd93c00,0x3aa73b64,0x387239a8,0x323e361f,0x323e0000,0x3872361f,0x3aa739a8,0x3bd93b64,0xbbd9bc00,0xbaa7bb64,0xb872b9a8,0xb23eb61f,
0xb61f8000,0xbb64b9a8,0xbb64bc00,0xb61fb9a8,0x361f8000,0x3b6439a8,0x3b643c00,0x361f39a8,0xb61f8000,0xbb64b9a8,0xbb64bc00,0xb61fb9a8,0x361f8000,0x3b6439a8,0x3b643c00,0x361f39a8,
0x3b643c00,0x361f39a8,0xb61f0000,0xbb64b9a8,0xbb64bc00,0xb61fb9a8,0x361f0000,0x3b6439a8,0x3b643c00,0x361f39a8,0xb61f0000,0xbb64b9a8,0xbb64bc00,0xb61fb9a8,0x361f0000,0x3b6439a8,
0xbaa7bc00,0x323eb61f,0x3bd939a8,0x38723b64,0x38728000,0x3bd93b64,0x323e39a8,0xbaa7b61f,0x3aa73c00,0xb23e361f,0xbbd9b9a8,0xb872bb64,0xb8728000,0xbbd9bb64,0xb23eb9a8,0x3aa7361f,
0xb8720000,0xbbd9bb64,0xb23eb9a8,0x3aa7361f,0xbaa7bc00,0x323eb61f,0x3bd939a8,0x38723b64,0x38720000,0x3bd93b64,0x323e39a8,0xbaa7b61f,0x3aa73c00,0xb23e361f,0xbbd9b9a8,0xb872bb64,
0x39a83c00,0xb9a80000,0xb9a8bc00,0x39a80000,0x39a83c00,0xb9a80000,0xb9a8bc00,0x39a80000,0x39a83c00,0xb9a80000,0xb9a8bc00,0x39a80000,0x39a83c00,0xb9a80000,0xb9a8bc00,0x39a80000,
0xb9a88000,0xb9a8bc00,0x39a88000,0x39a83c00,0xb9a88000,0xb9a8bc00,0x39a88000,0x39a83c00,0xb9a88000,0xb9a8bc00,0x39a88000,0x39a83c00,0xb9a88000,0xb9a8bc00,0x39a88000,0x39a83c00,
0xbaa70000,0xb23ebb64,0x3bd939a8,0xb872361f,0x38723c00,0xbbd9b61f,0x323eb9a8,0x3aa73b64,0x3aa70000,0x323e3b64,0xbbd9b9a8,0x3872b61f,0xb872bc00,0x3bd9361f,0xb23e39a8,0xbaa7bb64,
0xb872bc00,0x3bd9361f,0xb23e39a8,0xbaa7bb64,0xbaa78000,0xb23ebb64,0x3bd939a8,0xb872361f,0x38723c00,0xbbd9b61f,0x323eb9a8,0x3aa73b64,0x3aa78000,0x323e3b64,0xbbd9b9a8,0x3872b61f,
0x361f3c00,0xbb64b9a8,0x3b640000,0xb61f39a8,0xb61fbc00,0x3b6439a8,0xbb640000,0x361fb9a8,0x361f3c00,0xbb64b9a8,0x3b640000,0xb61f39a8,0xb61fbc00,0x3b6439a8,0xbb640000,0x361fb9a8,
0xbb648000,0x361fb9a8,0x361f3c00,0xbb64b9a8,0x3b648000,0xb61f39a8,0xb61fbc00,0x3b6439a8,0xbb648000,0x361fb9a8,0x361f3c00,0xbb64b9a8,0x3b648000,0xb61f39a8,0xb61fbc00,0x3b6439a8,
0xbbd90000,0x3aa7b61f,0xb87239a8,0x323ebb64,0xb23ebc00,0x38723b64,0xbaa7b9a8,0x3bd9361f,0x3bd90000,0xbaa7361f,0x3872b9a8,0xb23e3b64,0x323e3c00,0xb872bb64,0x3aa739a8,0xbbd9b61f,
0xb23ebc00,0x38723b64,0xbaa7b9a8,0x3bd9361f,0x3bd98000,0xbaa7361f,0x3872b9a8,0xb23e3b64,0x323e3c00,0xb872bb64,0x3aa739a8,0xbbd9b61f,0xbbd98000,0x3aa7b61f,0xb87239a8,0x323ebb64,
0xbc008000,0x3c008000,0xbc008000,0x3c008000,0xbc008000,0x3c008000,0xbc008000,0x3c008000,0xbc008000,0x3c008000,0xbc008000,0x3c008000,0xbc008000,0x3c008000,0xbc008000,0x3c008000,
0x3c00,0xbc00,0x3c00,0xbc00,0x3c00,0xbc00,0x3c00,0xbc00,0x3c00,0xbc00,0x3c00,0xbc00,0x3c00,0xbc00,0x3c00,0xbc00,
0x323ebc00,0xb8723b64,0x3aa7b9a8,0xbbd9361f,0xbbd98000,0x3aa7361f,0xb872b9a8,0x323e3b64,0xb23e3c00,0x3872bb64,0xbaa739a8,0x3bd9b61f,0x3bd98000,0xbaa7b61f,0x387239a8,0xb23ebb64,
0xbbd90000,0x3aa7361f,0xb872b9a8,0x323e3b64,0xb23e3c00,0x3872bb64,0xbaa739a8,0x3bd9b61f,0x3bd90000,0xbaa7b61f,0x387239a8,0xb23ebb64,0x323ebc00,0xb8723b64,0x3aa7b9a8,0xbbd9361f,
0xbb648000,0x361f39a8,0x361fbc00,0xbb6439a8,0x3b648000,0xb61fb9a8,0xb61f3c00,0x3b64b9a8,0xbb648000,0x361f39a8,0x361fbc00,0xbb6439a8,0x3b648000,0xb61fb9a8,0xb61f3c00,0x3b64b9a8,
0xb61f3c00,0x3b64b9a8,0xbb640000,0x361f39a8,0x361fbc00,0xbb6439a8,0x3b640000,0xb61fb9a8,0xb61f3c00,0x3b64b9a8,0xbb640000,0x361f39a8,0x361fbc00,0xbb6439a8,0x3b640000,0xb61fb9a8,
0x3872bc00,0xbbd9361f,0x323e39a8,0x3aa7bb64,0x3aa78000,0x323ebb64,0xbbd939a8,0x3872361f,0xb8723c00,0x3bd9b61f,0xb23eb9a8,0xbaa73b64,0xbaa78000,0xb23e3b64,0x3bd9b9a8,0xb872b61f,
0xbaa70000,0xb23e3b64,0x3bd9b9a8,0xb872b61f,0x3872bc00,0xbbd9361f,0x323e39a8,0x3aa7bb64,0x3aa70000,0x323ebb64,0xbbd939a8,0x3872361f,0xb8723c00,0x3bd9b61f,0xb23eb9a8,0xbaa73b64,
0xb9a83c00,0x39a80000,0x39a8bc00,0xb9a80000,0xb9a83c00,0x39a80000,0x39a8bc00,0xb9a80000,0xb9a83c00,0x39a80000,0x39a8bc00,0xb9a80000,0xb9a83c00,0x39a80000,0x39a8bc00,0xb9a80000,
0xb9a88000,0xb9a83c00,0x39a88000,0x39a8bc00,0xb9a88000,0xb9a83c00,0x39a88000,0x39a8bc00,0xb9a88000,0xb9a83c00,0x39a88000,0x39a8bc00,0xb9a88000,0xb9a83c00,0x39a88000,0x39a8bc00,
0xb8720000,0xbbd93b64,0xb23e39a8,0x3aa7b61f,0xbaa73c00,0x323e361f,0x3bd9b9a8,0x3872bb64,0x38720000,0x3bd9bb64,0x323eb9a8,0xbaa7361f,0x3aa7bc00,0xb23eb61f,0xbbd939a8,0xb8723b64,
0x3aa7bc00,0xb23eb61f,0xbbd939a8,0xb8723b64,0xb8728000,0xbbd93b64,0xb23e39a8,0x3aa7b61f,0xbaa73c00,0x323e361f,0x3bd9b9a8,0x3872bb64,0x38728000,0x3bd9bb64,0x323eb9a8,0xbaa7361f,
0xbb643c00,0xb61f39a8,0x361f0000,0x3b64b9a8,0x3b64bc00,0x361fb9a8,0xb61f0000,0xbb6439a8,0xbb643c00,0xb61f39a8,0x361f0000,0x3b64b9a8,0x3b64bc00,0x361fb9a8,0xb61f0000,0xbb6439a8,
0xb61f8000,0xbb6439a8,0xbb643c00,0xb61f39a8,0x361f8000,0x3b64b9a8,0x3b64bc00,0x361fb9a8,0xb61f8000,0xbb6439a8,0xbb643c00,0xb61f39a8,0x361f8000,0x3b64b9a8,0x3b64bc00,0x361fb9a8,
0xb23e0000,0xb872361f,0xbaa739a8,0xbbd93b64,0x3bd9bc00,0x3aa7bb64,0x3872b9a8,0x323eb61f,0x323e0000,0x3872b61f,0x3aa7b9a8,0x3bd9bb64,0xbbd93c00,0xbaa73b64,0xb87239a8,0xb23e361f,
0x3bd9bc00,0x3aa7bb64,0x3872b9a8,0x323eb61f,0x323e8000,0x3872b61f,0x3aa7b9a8,0x3bd9bb64,0xbbd93c00,0xbaa73b64,0xb87239a8,0xb23e361f,0xb23e8000,0xb872361f,0xbaa739a8,0xbbd93b64,
0x80008000,0x80008000,0x80008000,0x80008000,0x80008000,0x80008000,0x80008000,0x80008000,0x80008000,0x80008000,0x80008000,0x80008000,0x80008000,0x80008000,0x80008000,0x80008000,
0xbc003c00,0xbc003c00,0xbc003c00,0xbc003c00,0xbc003c00,0xbc003c00,0xbc003c00,0xbc003c00,0xbc003c00,0xbc003c00,0xbc003c00,0xbc003c00,0xbc003c00,0xbc003c00,0xbc003c00,0xbc003c00,
0x3bd9bc00,0x3aa7bb64,0x3872b9a8,0x323eb61f,0x323e8000,0x3872b61f,0x3aa7b9a8,0x3bd9bb64,0xbbd93c00,0xbaa73b64,0xb87239a8,0xb23e361f,0xb23e8000,0xb872361f,0xbaa739a8,0xbbd93b64,
0x323e0000,0x3872b61f,0x3aa7b9a8,0x3bd9bb64,0xbbd93c00,0xbaa73b64,0xb87239a8,0xb23e361f,0xb23e0000,0xb872361f,0xbaa739a8,0xbbd93b64,0x3bd9bc00,0x3aa7bb64,0x3872b9a8,0x323eb61f,
0x361f8000,0x3b64b9a8,0x3b64bc00,0x361fb9a8,0xb61f8000,0xbb6439a8,0xbb643c00,0xb61f39a8,0x361f8000,0x3b64b9a8,0x3b64bc00,0x361fb9a8,0xb61f8000,0xbb6439a8,0xbb643c00,0xb61f39a8,
0xbb643c00,0xb61f39a8,0x361f0000,0x3b64b9a8,0x3b64bc00,0x361fb9a8,0xb61f0000,0xbb6439a8,0xbb643c00,0xb61f39a8,0x361f0000,0x3b64b9a8,0x3b64bc00,0x361fb9a8,0xb61f0000,0xbb6439a8,
0x3aa7bc00,0xb23eb61f,0xbbd939a8,0xb8723b64,0xb8728000,0xbbd93b64,0xb23e39a8,0x3aa7b61f,0xbaa73c00,0x323e361f,0x3bd9b9a8,0x3872bb64,0x38728000,0x3bd9bb64,0x323eb9a8,0xbaa7361f,
0x38720000,0x3bd9bb64,0x323eb9a8,0xbaa7361f,0x3aa7bc00,0xb23eb61f,0xbbd939a8,0xb8723b64,0xb8720000,0xbbd93b64,0xb23e39a8,0x3aa7b61f,0xbaa73c00,0x323e361f,0x3bd9b9a8,0x3872bb64,
0xb9a83c00,0x39a80000,0x39a8bc00,0xb9a80000,0xb9a83c00,0x39a80000,0x39a8bc00,0xb9a80000,0xb9a83c00,0x39a80000,0x39a8bc00,0xb9a80000,0xb9a83c00,0x39a80000,0x39a8bc00,0xb9a80000,
0x39a88000,0x39a8bc00,0xb9a88000,0xb9a83c00,0x39a88000,0x39a8bc00,0xb9a88000,0xb9a83c00,0x39a88000,0x39a8bc00,0xb9a88000,0xb9a83c00,0x39a88000,0x39a8bc00,0xb9a88000,0xb9a83c00,
0x3aa70000,0x323ebb64,0xbbd939a8,0x3872361f,0xb8723c00,0x3bd9b61f,0xb23eb9a8,0xbaa73b64,0xbaa70000,0xb23e3b64,0x3bd9b9a8,0xb872b61f,0x3872bc00,0xbbd9361f,0x323e39a8,0x3aa7bb64,
0x3872bc00,0xbbd9361f,0x323e39a8,0x3aa7bb64,0x3aa78000,0x323ebb64,0xbbd939a8,0x3872361f,0xb8723c00,0x3bd9b61f,0xb23eb9a8,0xbaa73b64,0xbaa78000,0xb23e3b64,0x3bd9b9a8,0xb872b61f,
0xb61f3c00,0x3b64b9a8,0xbb640000,0x361f39a8,0x361fbc00,0xbb6439a8,0x3b640000,0xb61fb9a8,0xb61f3c00,0x3b64b9a8,0xbb640000,0x361f39a8,0x361fbc00,0xbb6439a8,0x3b640000,0xb61fb9a8,
0x3b648000,0xb61fb9a8,0xb61f3c00,0x3b64b9a8,0xbb648000,0x361f39a8,0x361fbc00,0xbb6439a8,0x3b648000,0xb61fb9a8,0xb61f3c00,0x3b64b9a8,0xbb648000,0x361f39a8,0x361fbc00,0xbb6439a8,
0x3bd90000,0xbaa7b61f,0x387239a8,0xb23ebb64,0x323ebc00,0xb8723b64,0x3aa7b9a8,0xbbd9361f,0xbbd90000,0x3aa7361f,0xb872b9a8,0x323e3b64,0xb23e3c00,0x3872bb64,0xbaa739a8,0x3bd9b61f,
0x323ebc00,0xb8723b64,0x3aa7b9a8,0xbbd9361f,0xbbd98000,0x3aa7361f,0xb872b9a8,0x323e3b64,0xb23e3c00,0x3872bb64,0xbaa739a8,0x3bd9b61f,0x3bd98000,0xbaa7b61f,0x387239a8,0xb23ebb64,
0x3c008000,0xbc008000,0x3c008000,0xbc008000,0x3c008000,0xbc008000,0x3c008000,0xbc008000,0x3c008000,0xbc008000,0x3c008000,0xbc008000,0x3c008000,0xbc008000,0x3c008000,0xbc008000,
0x3c00,0xbc00,0x3c00,0xbc00,0x3c00,0xbc00,0x3c00,0xbc00,0x3c00,0xbc00,0x3c00,0xbc00,0x3c00,0xbc00,0x3c00,0xbc00,
0xb23ebc00,0x38723b64,0xbaa7b9a8,0x3bd9361f,0x3bd98000,0xbaa7361f,0x3872b9a8,0xb23e3b64,0x323e3c00,0xb872bb64,0x3aa739a8,0xbbd9b61f,0xbbd98000,0x3aa7b61f,0xb87239a8,0x323ebb64,
0x3bd90000,0xbaa7361f,0x3872b9a8,0xb23e3b64,0x323e3c00,0xb872bb64,0x3aa739a8,0xbbd9b61f,0xbbd90000,0x3aa7b61f,0xb87239a8,0x323ebb64,0xb23ebc00,0x38723b64,0xbaa7b9a8,0x3bd9361f,
0x3b648000,0xb61f39a8,0xb61fbc00,0x3b6439a8,0xbb648000,0x361fb9a8,0x361f3c00,0xbb64b9a8,0x3b648000,0xb61f39a8,0xb61fbc00,0x3b6439a8,0xbb648000,0x361fb9a8,0x361f3c00,0xbb64b9a8,
0x361f3c00,0xbb64b9a8,0x3b640000,0xb61f39a8,0xb61fbc00,0x3b6439a8,0xbb640000,0x361fb9a8,0x361f3c00,0xbb64b9a8,0x3b640000,0xb61f39a8,0xb61fbc00,0x3b6439a8,0xbb640000,0x361fb9a8,
0xb872bc00,0x3bd9361f,0xb23e39a8,0xbaa7bb64,0xbaa78000,0xb23ebb64,0x3bd939a8,0xb872361f,0x38723c00,0xbbd9b61f,0x323eb9a8,0x3aa73b64,0x3aa78000,0x323e3b64,0xbbd9b9a8,0x3872b61f,
0x3aa70000,0x323e3b64,0xbbd9b9a8,0x3872b61f,0xb872bc00,0x3bd9361f,0xb23e39a8,0xbaa7bb64,0xbaa70000,0xb23ebb64,0x3bd939a8,0xb872361f,0x38723c00,0xbbd9b61f,0x323eb9a8,0x3aa73b64,
0x39a83c00,0xb9a80000,0xb9a8bc00,0x39a80000,0x39a83c00,0xb9a80000,0xb9a8bc00,0x39a80000,0x39a83c00,0xb9a80000,0xb9a8bc00,0x39a80000,0x39a83c00,0xb9a80000,0xb9a8bc00,0x39a80000,
0x39a88000,0x39a83c00,0xb9a88000,0xb9a8bc00,0x39a88000,0x39a83c00,0xb9a88000,0xb9a8bc00,0x39a88000,0x39a83c00,0xb9a88000,0xb9a8bc00,0x39a88000,0x39a83c00,0xb9a88000,0xb9a8bc00,
0x38720000,0x3bd93b64,0x323e39a8,0xbaa7b61f,0x3aa73c00,0xb23e361f,0xbbd9b9a8,0xb872bb64,0xb8720000,0xbbd9bb64,0xb23eb9a8,0x3aa7361f,0xbaa7bc00,0x323eb61f,0x3bd939a8,0x38723b64,
0xbaa7bc00,0x323eb61f,0x3bd939a8,0x38723b64,0x38728000,0x3bd93b64,0x323e39a8,0xbaa7b61f,0x3aa73c00,0xb23e361f,0xbbd9b9a8,0xb872bb64,0xb8728000,0xbbd9bb64,0xb23eb9a8,0x3aa7361f,
0x3b643c00,0x361f39a8,0xb61f0000,0xbb64b9a8,0xbb64bc00,0xb61fb9a8,0x361f0000,0x3b6439a8,0x3b643c00,0x361f39a8,0xb61f0000,0xbb64b9a8,0xbb64bc00,0xb61fb9a8,0x361f0000,0x3b6439a8,
0x361f8000,0x3b6439a8,0x3b643c00,0x361f39a8,0xb61f8000,0xbb64b9a8,0xbb64bc00,0xb61fb9a8,0x361f8000,0x3b6439a8,0x3b643c00,0x361f39a8,0xb61f8000,0xbb64b9a8,0xbb64bc00,0xb61fb9a8,
0x323e0000,0x3872361f,0x3aa739a8,0x3bd93b64,0xbbd9bc00,0xbaa7bb64,0xb872b9a8,0xb23eb61f,0xb23e0000,0xb872b61f,0xbaa7b9a8,0xbbd9bb64,0x3bd93c00,0x3aa73b64,0x387239a8,0x323e361f,
0xbbd9bc00,0xbaa7bb64,0xb872b9a8,0xb23eb61f,0xb23e8000,0xb872b61f,0xbaa7b9a8,0xbbd9bb64,0x3bd93c00,0x3aa73b64,0x387239a8,0x323e361f,0x323e8000,0x3872361f,0x3aa739a8,0x3bd93b64,
0x3d803d80,0x3d803d80,0x3d803d80,0x3d803d80,0x3d803d80,0x3d803d80,0x3d803d80,0x3d803d80,0x3d803d80,0x3d803d80,0x3d803d80,0x3d803d80,0x3d803d80,0x3d803d80,0x3d803d80,0x3d803d80,
0x80008000,0x80008000,0x80008000,0x80008000,0x80008000,0x80008000,0x80008000,0x80008000,0x80008000,0x80008000,0x80008000,0x80008000,0x80008000,0x80008000,0x80008000,0x80008000,
0xbc480000,0xbd0ebcc4,0xbd55bd35,0xbd7bbd6d,0x3d7b3d80,0x3d553d6d,0x3d0e3d35,0x3c483cc4,0x3c480000,0x3d0e3cc4,0x3d553d35,0x3d7b3d6d,0xbd7bbd80,0xbd55bd6d,0xbd0ebd35,0xbc48bcc4,
0xbd7bbd80,0xbd55bd6d,0xbd0ebd35,0xbc48bcc4,0xbc488000,0xbd0ebcc4,0xbd55bd35,0xbd7bbd6d,0x3d7b3d80,0x3d553d6d,0x3d0e3d35,0x3c483cc4,0x3c488000,0x3d0e3cc4,0x3d553d35,0x3d7b3d6d,
0x3d6d3d80,0x3cc43d35,0xbcc40000,0xbd6dbd35,0xbd6dbd80,0xbcc4bd35,0x3cc40000,0x3d6d3d35,0x3d6d3d80,0x3cc43d35,0xbcc40000,0xbd6dbd35,0xbd6dbd80,0xbcc4bd35,0x3cc40000,0x3d6d3d35,
0xbcc48000,0xbd6dbd35,0xbd6dbd80,0xbcc4bd35,0x3cc48000,0x3d6d3d35,0x3d6d3d80,0x3cc43d35,0xbcc48000,0xbd6dbd35,0xbd6dbd80,0xbcc4bd35,0x3cc48000,0x3d6d3d35,0x3d6d3d80,0x3cc43d35,
0xbd0e0000,0xbd7bbd6d,0xbc48bd35,0x3d553cc4,0xbd55bd80,0x3c48bcc4,0x3d7b3d35,0x3d0e3d6d,0x3d0e0000,0x3d7b3d6d,0x3c483d35,0xbd55bcc4,0x3d553d80,0xbc483cc4,0xbd7bbd35,0xbd0ebd6d,
0xbd55bd80,0x3c48bcc4,0x3d7b3d35,0x3d0e3d6d,0x3d0e8000,0x3d7b3d6d,0x3c483d35,0xbd55bcc4,0x3d553d80,0xbc483cc4,0xbd7bbd35,0xbd0ebd6d,0xbd0e8000,0xbd7bbd6d,0xbc48bd35,0x3d553cc4,
0xbd358000,0xbd35bd80,0x3d358000,0x3d353d80,0xbd358000,0xbd35bd80,0x3d358000,0x3d353d80,0xbd358000,0xbd35bd80,0x3d358000,0x3d353d80,0xbd358000,0xbd35bd80,0x3d358000,0x3d353d80,
0x3d353d80,0xbd350000,0xbd35bd80,0x3d350000,0x3d353d80,0xbd350000,0xbd35bd80,0x3d350000,0x3d353d80,0xbd350000,0xbd35bd80,0x3d350000,0x3d353d80,0xbd350000,0xbd35bd80,0x3d350000,
0xbd0ebd80,0x3d7b3cc4,0xbc483d35,0xbd55bd6d,0xbd558000,0xbc48bd6d,0x3d7b3d35,0xbd0e3cc4,0x3d0e3d80,0xbd7bbcc4,0x3c48bd35,0x3d553d6d,0x3d558000,0x3c483d6d,0xbd7bbd35,0x3d0ebcc4,
0xbd550000,0xbc48bd6d,0x3d7b3d35,0xbd0e3cc4,0x3d0e3d80,0xbd7bbcc4,0x3c48bd35,0x3d553d6d,0x3d550000,0x3c483d6d,0xbd7bbd35,0x3d0ebcc4,0xbd0ebd80,0x3d7b3cc4,0xbc483d35,0xbd55bd6d,
0xbd6d8000,0x3cc4bd35,0x3cc43d80,0xbd6dbd35,0x3d6d8000,0xbcc43d35,0xbcc4bd80,0x3d6d3d35,0xbd6d8000,0x3cc4bd35,0x3cc43d80,0xbd6dbd35,0x3d6d8000,0xbcc43d35,0xbcc4bd80,0x3d6d3d35,
0x3cc43d80,0xbd6dbd35,0x3d6d0000,0xbcc43d35,0xbcc4bd80,0x3d6d3d35,0xbd6d0000,0x3cc4bd35,0x3cc43d80,0xbd6dbd35,0x3d6d0000,0xbcc43d35,0xbcc4bd80,0x3d6d3d35,0xbd6d0000,0x3cc4bd35,
0xbc48bd80,0x3d0e3d6d,0xbd55bd35,0x3d7b3cc4,0x3d7b8000,0xbd553cc4,0x3d0ebd35,0xbc483d6d,0x3c483d80,0xbd0ebd6d,0x3d553d35,0xbd7bbcc4,0xbd7b8000,0x3d55bcc4,0xbd0e3d35,0x3c48bd6d,
0xbd7b0000,0x3d55bcc4,0xbd0e3d35,0x3c48bd6d,0xbc48bd80,0x3d0e3d6d,0xbd55bd35,0x3d7b3cc4,0x3d7b0000,0xbd553cc4,0x3d0ebd35,0xbc483d6d,0x3c483d80,0xbd0ebd6d,0x3d553d35,0xbd7bbcc4,
0x3d80,0xbd80,0x3d80,0xbd80,0x3d80,0xbd80,0x3d80,0xbd80,0x3d80,0xbd80,0x3d80,0xbd80,0x3d80,0xbd80,0x3d80,0xbd80,
0xbd808000,0x3d808000,0xbd808000,0x3d808000,0xbd808000,0x3d808000,0xbd808000,0x3d808000,0xbd808000,0x3d808000,0xbd808000,0x3d808000,0xbd808000,0x3d808000,0xbd808000,0x3d808000,
0xbd7b0000,0x3d553cc4,0xbd0ebd35,0x3c483d6d,0xbc483d80,0x3d0ebd6d,0xbd553d35,0x3d7bbcc4,0x3d7b0000,0xbd55bcc4,0x3d0e3d35,0xbc48bd6d,0x3c48bd80,0xbd0e3d6d,0x3d55bd35,0xbd7b3cc4,
0x3c48bd80,0xbd0e3d6d,0x3d55bd35,0xbd7b3cc4,0xbd7b8000,0x3d553cc4,0xbd0ebd35,0x3c483d6d,0xbc483d80,0x3d0ebd6d,0xbd553d35,0x3d7bbcc4,0x3d7b8000,0xbd55bcc4,0x3d0e3d35,0xbc48bd6d,
0xbcc43d80,0x3d6dbd35,0xbd6d0000,0x3cc43d35,0x3cc4bd80,0xbd6d3d35,0x3d6d0000,0xbcc4bd35,0xbcc43d80,0x3d6dbd35,0xbd6d0000,0x3cc43d35,0x3cc4bd80,0xbd6d3d35,0x3d6d0000,0xbcc4bd35,
0xbd6d8000,0x3cc43d35,0x3cc4bd80,0xbd6d3d35,0x3d6d8000,0xbcc4bd35,0xbcc43d80,0x3d6dbd35,0xbd6d8000,0x3cc43d35,0x3cc4bd80,0xbd6d3d35,0x3d6d8000,0xbcc4bd35,0xbcc43d80,0x3d6dbd35,
0xbd550000,0xbc483d6d,0x3d7bbd35,0xbd0ebcc4,0x3d0ebd80,0xbd7b3cc4,0x3c483d35,0x3d55bd6d,0x3d550000,0x3c48bd6d,0xbd7b3d35,0x3d0e3cc4,0xbd0e3d80,0x3d7bbcc4,0xbc48bd35,0xbd553d6d,
0x3d0ebd80,0xbd7b3cc4,0x3c483d35,0x3d55bd6d,0x3d558000,0x3c48bd6d,0xbd7b3d35,0x3d0e3cc4,0xbd0e3d80,0x3d7bbcc4,0xbc48bd35,0xbd553d6d,0xbd558000,0xbc483d6d,0x3d7bbd35,0xbd0ebcc4,
0xbd358000,0xbd353d80,0x3d358000,0x3d35bd80,0xbd358000,0xbd353d80,0x3d358000,0x3d35bd80,0xbd358000,0xbd353d80,0x3d358000,0x3d35bd80,0xbd358000,0xbd353d80,0x3d358000,0x3d35bd80,
0xbd353d80,0x3d350000,0x3d35bd80,0xbd350000,0xbd353d80,0x3d350000,0x3d35bd80,0xbd350000,0xbd353d80,0x3d350000,0x3d35bd80,0xbd350000,0xbd353d80,0x3d350000,0x3d35bd80,0xbd350000,
0x3d55bd80,0xbc48bcc4,0xbd7b3d35,0xbd0e3d6d,0xbd0e8000,0xbd7b3d6d,0xbc483d35,0x3d55bcc4,0xbd553d80,0x3c483cc4,0x3d7bbd35,0x3d0ebd6d,0x3d0e8000,0x3d7bbd6d,0x3c48bd35,0xbd553cc4,
0xbd0e0000,0xbd7b3d6d,0xbc483d35,0x3d55bcc4,0xbd553d80,0x3c483cc4,0x3d7bbd35,0x3d0ebd6d,0x3d0e0000,0x3d7bbd6d,0x3c48bd35,0xbd553cc4,0x3d55bd80,0xbc48bcc4,0xbd7b3d35,0xbd0e3d6d,
0xbcc48000,0xbd6d3d35,0xbd6d3d80,0xbcc43d35,0x3cc48000,0x3d6dbd35,0x3d6dbd80,0x3cc4bd35,0xbcc48000,0xbd6d3d35,0xbd6d3d80,0xbcc43d35,0x3cc48000,0x3d6dbd35,0x3d6dbd80,0x3cc4bd35,
0xbd6d3d80,0xbcc43d35,0x3cc40000,0x3d6dbd35,0x3d6dbd80,0x3cc4bd35,0xbcc40000,0xbd6d3d35,0xbd6d3d80,0xbcc43d35,0x3cc40000,0x3d6dbd35,0x3d6dbd80,0x3cc4bd35,0xbcc40000,0xbd6d3d35,
0x3d7bbd80,0x3d55bd6d,0x3d0ebd35,0x3c48bcc4,0x3c488000,0x3d0ebcc4,0x3d55bd35,0x3d7bbd6d,0xbd7b3d80,0xbd553d6d,0xbd0e3d35,0xbc483cc4,0xbc488000,0xbd0e3cc4,0xbd553d35,0xbd7b3d6d,
0xbc480000,0xbd0e3cc4,0xbd553d35,0xbd7b3d6d,0x3d7bbd80,0x3d55bd6d,0x3d0ebd35,0x3c48bcc4,0x3c480000,0x3d0ebcc4,0x3d55bd35,0x3d7bbd6d,0xbd7b3d80,0xbd553d6d,0xbd0e3d35,0xbc483cc4,
0xbd803d80,0xbd803d80,0xbd803d80,0xbd803d80,0xbd803d80,0xbd803d80,0xbd803d80,0xbd803d80,0xbd803d80,0xbd803d80,0xbd803d80,0xbd803d80,0xbd803d80,0xbd803d80,0xbd803d80,0xbd803d80,
0x80008000,0x80008000,0x80008000,0x80008000,0x80008000,0x80008000,0x80008000,0x80008000,0x80008000,0x80008000,0x80008000,0x80008000,0x80008000,0x80008000,0x80008000,0x80008000,
0x3c480000,0x3d0ebcc4,0x3d55bd35,0x3d7bbd6d,0xbd7b3d80,0xbd553d6d,0xbd0e3d35,0xbc483cc4,0xbc480000,0xbd0e3cc4,0xbd553d35,0xbd7b3d6d,0x3d7bbd80,0x3d55bd6d,0x3d0ebd35,0x3c48bcc4,
0x3d7bbd80,0x3d55bd6d,0x3d0ebd35,0x3c48bcc4,0x3c488000,0x3d0ebcc4,0x3d55bd35,0x3d7bbd6d,0xbd7b3d80,0xbd553d6d,0xbd0e3d35,0xbc483cc4,0xbc488000,0xbd0e3cc4,0xbd553d35,0xbd7b3d6d,
0xbd6d3d80,0xbcc43d35,0x3cc40000,0x3d6dbd35,0x3d6dbd80,0x3cc4bd35,0xbcc40000,0xbd6d3d35,0xbd6d3d80,0xbcc43d35,0x3cc40000,0x3d6dbd35,0x3d6dbd80,0x3cc4bd35,0xbcc40000,0xbd6d3d35,
0x3cc48000,0x3d6dbd35,0x3d6dbd80,0x3cc4bd35,0xbcc48000,0xbd6d3d35,0xbd6d3d80,0xbcc43d35,0x3cc48000,0x3d6dbd35,0x3d6dbd80,0x3cc4bd35,0xbcc48000,0xbd6d3d35,0xbd6d3d80,0xbcc43d35,
0x3d0e0000,0x3d7bbd6d,0x3c48bd35,0xbd553cc4,0x3d55bd80,0xbc48bcc4,0xbd7b3d35,0xbd0e3d6d,0xbd0e0000,0xbd7b3d6d,0xbc483d35,0x3d55bcc4,0xbd553d80,0x3c483cc4,0x3d7bbd35,0x3d0ebd6d,
0x3d55bd80,0xbc48bcc4,0xbd7b3d35,0xbd0e3d6d,0xbd0e8000,0xbd7b3d6d,0xbc483d35,0x3d55bcc4,0xbd553d80,0x3c483cc4,0x3d7bbd35,0x3d0ebd6d,0x3d0e8000,0x3d7bbd6d,0x3c48bd35,0xbd553cc4,
0x3d358000,0x3d35bd80,0xbd358000,0xbd353d80,0x3d358000,0x3d35bd80,0xbd358000,0xbd353d80,0x3d358000,0x3d35bd80,0xbd358000,0xbd353d80,0x3d358000,0x3d35bd80,0xbd358000,0xbd353d80,
0xbd353d80,0x3d350000,0x3d35bd80,0xbd350000,0xbd353d80,0x3d350000,0x3d35bd80,0xbd350000,0xbd353d80,0x3d350000,0x3d35bd80,0xbd350000,0xbd353d80,0x3d350000,0x3d35bd80,0xbd350000,
0x3d0ebd80,0xbd7b3cc4,0x3c483d35,0x3d55bd6d,0x3d558000,0x3c48bd6d,0xbd7b3d35,0x3d0e3cc4,0xbd0e3d80,0x3d7bbcc4,0xbc48bd35,0xbd553d6d,0xbd558000,0xbc483d6d,0x3d7bbd35,0xbd0ebcc4,
0x3d550000,0x3c48bd6d,0xbd7b3d35,0x3d0e3cc4,0xbd0e3d80,0x3d7bbcc4,0xbc48bd35,0xbd553d6d,0xbd550000,0xbc483d6d,0x3d7bbd35,0xbd0ebcc4,0x3d0ebd80,0xbd7b3cc4,0x3c483d35,0x3d55bd6d,
0x3d6d8000,0xbcc4bd35,0xbcc43d80,0x3d6dbd35,0xbd6d8000,0x3cc43d35,0x3cc4bd80,0xbd6d3d35,0x3d6d8000,0xbcc4bd35,0xbcc43d80,0x3d6dbd35,0xbd6d8000,0x3cc43d35,0x3cc4bd80,0xbd6d3d35,
0xbcc43d80,0x3d6dbd35,0xbd6d0000,0x3cc43d35,0x3cc4bd80,0xbd6d3d35,0x3d6d0000,0xbcc4bd35,0xbcc43d80,0x3d6dbd35,0xbd6d0000,0x3cc43d35,0x3cc4bd80,0xbd6d3d35,0x3d6d0000,0xbcc4bd35,
0x3c48bd80,0xbd0e3d6d,0x3d55bd35,0xbd7b3cc4,0xbd7b8000,0x3d553cc4,0xbd0ebd35,0x3c483d6d,0xbc483d80,0x3d0ebd6d,0xbd553d35,0x3d7bbcc4,0x3d7b8000,0xbd55bcc4,0x3d0e3d35,0xbc48bd6d,
0x3d7b0000,0xbd55bcc4,0x3d0e3d35,0xbc48bd6d,0x3c48bd80,0xbd0e3d6d,0x3d55bd35,0xbd7b3cc4,0xbd7b0000,0x3d553cc4,0xbd0ebd35,0x3c483d6d,0xbc483d80,0x3d0ebd6d,0xbd553d35,0x3d7bbcc4,
0x3d80,0xbd80,0x3d80,0xbd80,0x3d80,0xbd80,0x3d80,0xbd80,0x3d80,0xbd80,0x3d80,0xbd80,0x3d80,0xbd80,0x3d80,0xbd80,
0x3d808000,0xbd808000,0x3d808000,0xbd808000,0x3d808000,0xbd808000,0x3d808000,0xbd808000,0x3d808000,0xbd808000,0x3d808000,0xbd808000,0x3d808000,0xbd808000,0x3d808000,0xbd808000,
0x3d7b0000,0xbd553cc4,0x3d0ebd35,0xbc483d6d,0x3c483d80,0xbd0ebd6d,0x3d553d35,0xbd7bbcc4,0xbd7b0000,0x3d55bcc4,0xbd0e3d35,0x3c48bd6d,0xbc48bd80,0x3d0e3d6d,0xbd55bd35,0x3d7b3cc4,
0xbc48bd80,0x3d0e3d6d,0xbd55bd35,0x3d7b3cc4,0x3d7b8000,0xbd553cc4,0x3d0ebd35,0xbc483d6d,0x3c483d80,0xbd0ebd6d,0x3d553d35,0xbd7bbcc4,0xbd7b8000,0x3d55bcc4,0xbd0e3d35,0x3c48bd6d,
0x3cc43d80,0xbd6dbd35,0x3d6d0000,0xbcc43d35,0xbcc4bd80,0x3d6d3d35,0xbd6d0000,0x3cc4bd35,0x3cc43d80,0xbd6dbd35,0x3d6d0000,0xbcc43d35,0xbcc4bd80,0x3d6d3d35,0xbd6d0000,0x3cc4bd35,
0x3d6d8000,0xbcc43d35,0xbcc4bd80,0x3d6d3d35,0xbd6d8000,0x3cc4bd35,0x3cc43d80,0xbd6dbd35,0x3d6d8000,0xbcc43d35,0xbcc4bd80,0x3d6d3d35,0xbd6d8000,0x3cc4bd35,0x3cc43d80,0xbd6dbd35,
0x3d550000,0x3c483d6d,0xbd7bbd35,0x3d0ebcc4,0xbd0ebd80,0x3d7b3cc4,0xbc483d35,0xbd55bd6d,0xbd550000,0xbc48bd6d,0x3d7b3d35,0xbd0e3cc4,0x3d0e3d80,0xbd7bbcc4,0x3c48bd35,0x3d553d6d,
0xbd0ebd80,0x3d7b3cc4,0xbc483d35,0xbd55bd6d,0xbd558000,0xbc48bd6d,0x3d7b3d35,0xbd0e3cc4,0x3d0e3d80,0xbd7bbcc4,0x3c48bd35,0x3d553d6d,0x3d558000,0x3c483d6d,0xbd7bbd35,0x3d0ebcc4,
0x3d358000,0x3d353d80,0xbd358000,0xbd35bd80,0x3d358000,0x3d353d80,0xbd358000,0xbd35bd80,0x3d358000,0x3d353d80,0xbd358000,0xbd35bd80,0x3d358000,0x3d353d80,0xbd358000,0xbd35bd80,
0x3d353d80,0xbd350000,0xbd35bd80,0x3d350000,0x3d353d80,0xbd350000,0xbd35bd80,0x3d350000,0x3d353d80,0xbd350000,0xbd35bd80,0x3d350000,0x3d353d80,0xbd350000,0xbd35bd80,0x3d350000,
0xbd55bd80,0x3c48bcc4,0x3d7b3d35,0x3d0e3d6d,0x3d0e8000,0x3d7b3d6d,0x3c483d35,0xbd55bcc4,0x3d553d80,0xbc483cc4,0xbd7bbd35,0xbd0ebd6d,0xbd0e8000,0xbd7bbd6d,0xbc48bd35,0x3d553cc4,
0x3d0e0000,0x3d7b3d6d,0x3c483d35,0xbd55bcc4,0x3d553d80,0xbc483cc4,0xbd7bbd35,0xbd0ebd6d,0xbd0e0000,0xbd7bbd6d,0xbc48bd35,0x3d553cc4,0xbd55bd80,0x3c48bcc4,0x3d7b3d35,0x3d0e3d6d,
0x3cc48000,0x3d6d3d35,0x3d6d3d80,0x3cc43d35,0xbcc48000,0xbd6dbd35,0xbd6dbd80,0xbcc4bd35,0x3cc48000,0x3d6d3d35,0x3d6d3d80,0x3cc43d35,0xbcc48000,0xbd6dbd35,0xbd6dbd80,0xbcc4bd35,
0x3d6d3d80,0x3cc43d35,0xbcc40000,0xbd6dbd35,0xbd6dbd80,0xbcc4bd35,0x3cc40000,0x3d6d3d35,0x3d6d3d80,0x3cc43d35,0xbcc40000,0xbd6dbd35,0xbd6dbd80,0xbcc4bd35,0x3cc40000,0x3d6d3d35,
0xbd7bbd80,0xbd55bd6d,0xbd0ebd35,0xbc48bcc4,0xbc488000,0xbd0ebcc4,0xbd55bd35,0xbd7bbd6d,0x3d7b3d80,0x3d553d6d,0x3d0e3d35,0x3c483cc4,0x3c488000,0x3d0e3cc4,0x3d553d35,0x3d7b3d6d,
0x3c480000,0x3d0e3cc4,0x3d553d35,0x3d7b3d6d,0xbd7bbd80,0xbd55bd6d,0xbd0ebd35,0xbc48bcc4,0xbc480000,0xbd0ebcc4,0xbd55bd35,0xbd7bbd6d,0x3d7b3d80,0x3d553d6d,0x3d0e3d35,0x3c483cc4,
0,0,0,0,0,0,0,0,0,0,0,0,0,0,0,0,
0x3d803d80,0x3d803d80,0x3d803d80,0x3d803d80,0x3d803d80,0x3d803d80,0x3d803d80,0x3d803d80,0x3d803d80,0x3d803d80,0x3d803d80,0x3d803d80,0x3d803d80,0x3d803d80,0x3d803d80,0x3d803d80,
0x3d7b3d80,0x3d553d6d,0x3d0e3d35,0x3c483cc4,0x3c480000,0x3d0e3cc4,0x3d553d35,0x3d7b3d6d,0xbd7bbd80,0xbd55bd6d,0xbd0ebd35,0xbc48bcc4,0xbc480000,0xbd0ebcc4,0xbd55bd35,0xbd7bbd6d,
0xbc480000,0xbd0ebcc4,0xbd55bd35,0xbd7bbd6d,0x3d7b3d80,0x3d553d6d,0x3d0e3d35,0x3c483cc4,0x3c480000,0x3d0e3cc4,0x3d553d35,0x3d7b3d6d,0xbd7bbd80,0xbd55bd6d,0xbd0ebd35,0xbc48bcc4,
0x3cc40000,0x3d6d3d35,0x3d6d3d80,0x3cc43d35,0xbcc40000,0xbd6dbd35,0xbd6dbd80,0xbcc4bd35,0x3cc40000,0x3d6d3d35,0x3d6d3d80,0x3cc43d35,0xbcc40000,0xbd6dbd35,0xbd6dbd80,0xbcc4bd35,
0x3d6d3d80,0x3cc43d35,0xbcc40000,0xbd6dbd35,0xbd6dbd80,0xbcc4bd35,0x3cc40000,0x3d6d3d35,0x3d6d3d80,0x3cc43d35,0xbcc40000,0xbd6dbd35,0xbd6dbd80,0xbcc4bd35,0x3cc40000,0x3d6d3d35,
0x3d553d80,0xbc483cc4,0xbd7bbd35,0xbd0ebd6d,0xbd0e0000,0xbd7bbd6d,0xbc48bd35,0x3d553cc4,0xbd55bd80,0x3c48bcc4,0x3d7b3d35,0x3d0e3d6d,0x3d0e0000,0x3d7b3d6d,0x3c483d35,0xbd55bcc4,
0xbd0e0000,0xbd7bbd6d,0xbc48bd35,0x3d553cc4,0xbd55bd80,0x3c48bcc4,0x3d7b3d35,0x3d0e3d6d,0x3d0e0000,0x3d7b3d6d,0x3c483d35,0xbd55bcc4,0x3d553d80,0xbc483cc4,0xbd7bbd35,0xbd0ebd6d,
0x3d353d80,0xbd350000,0xbd35bd80,0x3d350000,0x3d353d80,0xbd350000,0xbd35bd80,0x3d350000,0x3d353d80,0xbd350000,0xbd35bd80,0x3d350000,0x3d353d80,0xbd350000,0xbd35bd80,0x3d350000,
0x3d350000,0x3d353d80,0xbd350000,0xbd35bd80,0x3d350000,0x3d353d80,0xbd350000,0xbd35bd80,0x3d350000,0x3d353d80,0xbd350000,0xbd35bd80,0x3d350000,0x3d353d80,0xbd350000,0xbd35bd80,
0xbd550000,0xbc48bd6d,0x3d7b3d35,0xbd0e3cc4,0x3d0e3d80,0xbd7bbcc4,0x3c48bd35,0x3d553d6d,0x3d550000,0x3c483d6d,0xbd7bbd35,0x3d0ebcc4,0xbd0ebd80,0x3d7b3cc4,0xbc483d35,0xbd55bd6d,
0x3d0e3d80,0xbd7bbcc4,0x3c48bd35,0x3d553d6d,0x3d550000,0x3c483d6d,0xbd7bbd35,0x3d0ebcc4,0xbd0ebd80,0x3d7b3cc4,0xbc483d35,0xbd55bd6d,0xbd550000,0xbc48bd6d,0x3d7b3d35,0xbd0e3cc4,
0x3cc43d80,0xbd6dbd35,0x3d6d0000,0xbcc43d35,0xbcc4bd80,0x3d6d3d35,0xbd6d0000,0x3cc4bd35,0x3cc43d80,0xbd6dbd35,0x3d6d0000,0xbcc43d35,0xbcc4bd80,0x3d6d3d35,0xbd6d0000,0x3cc4bd35,
0x3d6d0000,0xbcc43d35,0xbcc4bd80,0x3d6d3d35,0xbd6d0000,0x3cc4bd35,0x3cc43d80,0xbd6dbd35,0x3d6d0000,0xbcc43d35,0xbcc4bd80,0x3d6d3d35,0xbd6d0000,0x3cc4bd35,0x3cc43d80,0xbd6dbd35,
0xbd7b0000,0x3d55bcc4,0xbd0e3d35,0x3c48bd6d,0xbc48bd80,0x3d0e3d6d,0xbd55bd35,0x3d7b3cc4,0x3d7b0000,0xbd553cc4,0x3d0ebd35,0xbc483d6d,0x3c483d80,0xbd0ebd6d,0x3d553d35,0xbd7bbcc4,
0x3c483d80,0xbd0ebd6d,0x3d553d35,0xbd7bbcc4,0xbd7b0000,0x3d55bcc4,0xbd0e3d35,0x3c48bd6d,0xbc48bd80,0x3d0e3d6d,0xbd55bd35,0x3d7b3cc4,0x3d7b0000,0xbd553cc4,0x3d0ebd35,0xbc483d6d,
0x3d800000,0xbd800000,0x3d800000,0xbd800000,0x3d800000,0xbd800000,0x3d800000,0xbd800000,0x3d800000,0xbd800000,0x3d800000,0xbd800000,0x3d800000,0xbd800000,0x3d800000,0xbd800000,
0x3d80,0xbd80,0x3d80,0xbd80,0x3d80,0xbd80,0x3d80,0xbd80,0x3d80,0xbd80,0x3d80,0xbd80,0x3d80,0xbd80,0x3d80,0xbd80,
0xbc483d80,0x3d0ebd6d,0xbd553d35,0x3d7bbcc4,0x3d7b0000,0xbd55bcc4,0x3d0e3d35,0xbc48bd6d,0x3c48bd80,0xbd0e3d6d,0x3d55bd35,0xbd7b3cc4,0xbd7b0000,0x3d553cc4,0xbd0ebd35,0x3c483d6d,
0xbd7b0000,0x3d553cc4,0xbd0ebd35,0x3c483d6d,0xbc483d80,0x3d0ebd6d,0xbd553d35,0x3d7bbcc4,0x3d7b0000,0xbd55bcc4,0x3d0e3d35,0xbc48bd6d,0x3c48bd80,0xbd0e3d6d,0x3d55bd35,0xbd7b3cc4,
0x3d6d0000,0xbcc4bd35,0xbcc43d80,0x3d6dbd35,0xbd6d0000,0x3cc43d35,0x3cc4bd80,0xbd6d3d35,0x3d6d0000,0xbcc4bd35,0xbcc43d80,0x3d6dbd35,0xbd6d0000,0x3cc43d35,0x3cc4bd80,0xbd6d3d35,
0xbcc43d80,0x3d6dbd35,0xbd6d0000,0x3cc43d35,0x3cc4bd80,0xbd6d3d35,0x3d6d0000,0xbcc4bd35,0xbcc43d80,0x3d6dbd35,0xbd6d0000,0x3cc43d35,0x3cc4bd80,0xbd6d3d35,0x3d6d0000,0xbcc4bd35,
0xbd0e3d80,0x3d7bbcc4,0xbc48bd35,0xbd553d6d,0xbd550000,0xbc483d6d,0x3d7bbd35,0xbd0ebcc4,0x3d0ebd80,0xbd7b3cc4,0x3c483d35,0x3d55bd6d,0x3d550000,0x3c48bd6d,0xbd7b3d35,0x3d0e3cc4,
0xbd550000,0xbc483d6d,0x3d7bbd35,0xbd0ebcc4,0x3d0ebd80,0xbd7b3cc4,0x3c483d35,0x3d55bd6d,0x3d550000,0x3c48bd6d,0xbd7b3d35,0x3d0e3cc4,0xbd0e3d80,0x3d7bbcc4,0xbc48bd35,0xbd553d6d,
0xbd353d80,0x3d350000,0x3d35bd80,0xbd350000,0xbd353d80,0x3d350000,0x3d35bd80,0xbd350000,0xbd353d80,0x3d350000,0x3d35bd80,0xbd350000,0xbd353d80,0x3d350000,0x3d35bd80,0xbd350000,
0x3d350000,0x3d35bd80,0xbd350000,0xbd353d80,0x3d350000,0x3d35bd80,0xbd350000,0xbd353d80,0x3d350000,0x3d35bd80,0xbd350000,0xbd353d80,0x3d350000,0x3d35bd80,0xbd350000,0xbd353d80,
0xbd0e0000,0xbd7b3d6d,0xbc483d35,0x3d55bcc4,0xbd553d80,0x3c483cc4,0x3d7bbd35,0x3d0ebd6d,0x3d0e0000,0x3d7bbd6d,0x3c48bd35,0xbd553cc4,0x3d55bd80,0xbc48bcc4,0xbd7b3d35,0xbd0e3d6d,
0xbd553d80,0x3c483cc4,0x3d7bbd35,0x3d0ebd6d,0x3d0e0000,0x3d7bbd6d,0x3c48bd35,0xbd553cc4,0x3d55bd80,0xbc48bcc4,0xbd7b3d35,0xbd0e3d6d,0xbd0e0000,0xbd7b3d6d,0xbc483d35,0x3d55bcc4,
0xbd6d3d80,0xbcc43d35,0x3cc40000,0x3d6dbd35,0x3d6dbd80,0x3cc4bd35,0xbcc40000,0xbd6d3d35,0xbd6d3d80,0xbcc43d35,0x3cc40000,0x3d6dbd35,0x3d6dbd80,0x3cc4bd35,0xbcc40000,0xbd6d3d35,
0x3cc40000,0x3d6dbd35,0x3d6dbd80,0x3cc4bd35,0xbcc40000,0xbd6d3d35,0xbd6d3d80,0xbcc43d35,0x3cc40000,0x3d6dbd35,0x3d6dbd80,0x3cc4bd35,0xbcc40000,0xbd6d3d35,0xbd6d3d80,0xbcc43d35,
0xbc480000,0xbd0e3cc4,0xbd553d35,0xbd7b3d6d,0x3d7bbd80,0x3d55bd6d,0x3d0ebd35,0x3c48bcc4,0x3c480000,0x3d0ebcc4,0x3d55bd35,0x3d7bbd6d,0xbd7b3d80,0xbd553d6d,0xbd0e3d35,0xbc483cc4,
0xbd7b3d80,0xbd553d6d,0xbd0e3d35,0xbc483cc4,0xbc480000,0xbd0e3cc4,0xbd553d35,0xbd7b3d6d,0x3d7bbd80,0x3d55bd6d,0x3d0ebd35,0x3c48bcc4,0x3c480000,0x3d0ebcc4,0x3d55bd35,0x3d7bbd6d,
0,0,0,0,0,0,0,0,0,0,0,0,0,0,0,0,
0xbd803d80,0xbd803d80,0xbd803d80,0xbd803d80,0xbd803d80,0xbd803d80,0xbd803d80,0xbd803d80,0xbd803d80,0xbd803d80,0xbd803d80,0xbd803d80,0xbd803d80,0xbd803d80,0xbd803d80,0xbd803d80,
0xbd7b3d80,0xbd553d6d,0xbd0e3d35,0xbc483cc4,0xbc480000,0xbd0e3cc4,0xbd553d35,0xbd7b3d6d,0x3d7bbd80,0x3d55bd6d,0x3d0ebd35,0x3c48bcc4,0x3c480000,0x3d0ebcc4,0x3d55bd35,0x3d7bbd6d,
0x3c480000,0x3d0ebcc4,0x3d55bd35,0x3d7bbd6d,0xbd7b3d80,0xbd553d6d,0xbd0e3d35,0xbc483cc4,0xbc480000,0xbd0e3cc4,0xbd553d35,0xbd7b3d6d,0x3d7bbd80,0x3d55bd6d,0x3d0ebd35,0x3c48bcc4,
0xbcc40000,0xbd6d3d35,0xbd6d3d80,0xbcc43d35,0x3cc40000,0x3d6dbd35,0x3d6dbd80,0x3cc4bd35,0xbcc40000,0xbd6d3d35,0xbd6d3d80,0xbcc43d35,0x3cc40000,0x3d6dbd35,0x3d6dbd80,0x3cc4bd35,
0xbd6d3d80,0xbcc43d35,0x3cc40000,0x3d6dbd35,0x3d6dbd80,0x3cc4bd35,0xbcc40000,0xbd6d3d35,0xbd6d3d80,0xbcc43d35,0x3cc40000,0x3d6dbd35,0x3d6dbd80,0x3cc4bd35,0xbcc40000,0xbd6d3d35,
0xbd553d80,0x3c483cc4,0x3d7bbd35,0x3d0ebd6d,0x3d0e0000,0x3d7bbd6d,0x3c48bd35,0xbd553cc4,0x3d55bd80,0xbc48bcc4,0xbd7b3d35,0xbd0e3d6d,0xbd0e0000,0xbd7b3d6d,0xbc483d35,0x3d55bcc4,
0x3d0e0000,0x3d7bbd6d,0x3c48bd35,0xbd553cc4,0x3d55bd80,0xbc48bcc4,0xbd7b3d35,0xbd0e3d6d,0xbd0e0000,0xbd7b3d6d,0xbc483d35,0x3d55bcc4,0xbd553d80,0x3c483cc4,0x3d7bbd35,0x3d0ebd6d,
0xbd353d80,0x3d350000,0x3d35bd80,0xbd350000,0xbd353d80,0x3d350000,0x3d35bd80,0xbd350000,0xbd353d80,0x3d350000,0x3d35bd80,0xbd350000,0xbd353d80,0x3d350000,0x3d35bd80,0xbd350000,
0xbd350000,0xbd353d80,0x3d350000,0x3d35bd80,0xbd350000,0xbd353d80,0x3d350000,0x3d35bd80,0xbd350000,0xbd353d80,0x3d350000,0x3d35bd80,0xbd350000,0xbd353d80,0x3d350000,0x3d35bd80,
0x3d550000,0x3c48bd6d,0xbd7b3d35,0x3d0e3cc4,0xbd0e3d80,0x3d7bbcc4,0xbc48bd35,0xbd553d6d,0xbd550000,0xbc483d6d,0x3d7bbd35,0xbd0ebcc4,0x3d0ebd80,0xbd7b3cc4,0x3c483d35,0x3d55bd6d,
0xbd0e3d80,0x3d7bbcc4,0xbc48bd35,0xbd553d6d,0xbd550000,0xbc483d6d,0x3d7bbd35,0xbd0ebcc4,0x3d0ebd80,0xbd7b3cc4,0x3c483d35,0x3d55bd6d,0x3d550000,0x3c48bd6d,0xbd7b3d35,0x3d0e3cc4,
0xbcc43d80,0x3d6dbd35,0xbd6d0000,0x3cc43d35,0x3cc4bd80,0xbd6d3d35,0x3d6d0000,0xbcc4bd35,0xbcc43d80,0x3d6dbd35,0xbd6d0000,0x3cc43d35,0x3cc4bd80,0xbd6d3d35,0x3d6d0000,0xbcc4bd35,
0xbd6d0000,0x3cc43d35,0x3cc4bd80,0xbd6d3d35,0x3d6d0000,0xbcc4bd35,0xbcc43d80,0x3d6dbd35,0xbd6d0000,0x3cc43d35,0x3cc4bd80,0xbd6d3d35,0x3d6d0000,0xbcc4bd35,0xbcc43d80,0x3d6dbd35,
0x3d7b0000,0xbd55bcc4,0x3d0e3d35,0xbc48bd6d,0x3c48bd80,0xbd0e3d6d,0x3d55bd35,0xbd7b3cc4,0xbd7b0000,0x3d553cc4,0xbd0ebd35,0x3c483d6d,0xbc483d80,0x3d0ebd6d,0xbd553d35,0x3d7bbcc4,
0xbc483d80,0x3d0ebd6d,0xbd553d35,0x3d7bbcc4,0x3d7b0000,0xbd55bcc4,0x3d0e3d35,0xbc48bd6d,0x3c48bd80,0xbd0e3d6d,0x3d55bd35,0xbd7b3cc4,0xbd7b0000,0x3d553cc4,0xbd0ebd35,0x3c483d6d,
0xbd800000,0x3d800000,0xbd800000,0x3d800000,0xbd800000,0x3d800000,0xbd800000,0x3d800000,0xbd800000,0x3d800000,0xbd800000,0x3d800000,0xbd800000,0x3d800000,0xbd800000,0x3d800000,
0x3d80,0xbd80,0x3d80,0xbd80,0x3d80,0xbd80,0x3d80,0xbd80,0x3d80,0xbd80,0x3d80,0xbd80,0x3d80,0xbd80,0x3d80,0xbd80,
0x3c483d80,0xbd0ebd6d,0x3d553d35,0xbd7bbcc4,0xbd7b0000,0x3d55bcc4,0xbd0e3d35,0x3c48bd6d,0xbc48bd80,0x3d0e3d6d,0xbd55bd35,0x3d7b3cc4,0x3d7b0000,0xbd553cc4,0x3d0ebd35,0xbc483d6d,
0x3d7b0000,0xbd553cc4,0x3d0ebd35,0xbc483d6d,0x3c483d80,0xbd0ebd6d,0x3d553d35,0xbd7bbcc4,0xbd7b0000,0x3d55bcc4,0xbd0e3d35,0x3c48bd6d,0xbc48bd80,0x3d0e3d6d,0xbd55bd35,0x3d7b3cc4,
0xbd6d0000,0x3cc4bd35,0x3cc43d80,0xbd6dbd35,0x3d6d0000,0xbcc43d35,0xbcc4bd80,0x3d6d3d35,0xbd6d0000,0x3cc4bd35,0x3cc43d80,0xbd6dbd35,0x3d6d0000,0xbcc43d35,0xbcc4bd80,0x3d6d3d35,
0x3cc43d80,0xbd6dbd35,0x3d6d0000,0xbcc43d35,0xbcc4bd80,0x3d6d3d35,0xbd6d0000,0x3cc4bd35,0x3cc43d80,0xbd6dbd35,0x3d6d0000,0xbcc43d35,0xbcc4bd80,0x3d6d3d35,0xbd6d0000,0x3cc4bd35,
0x3d0e3d80,0xbd7bbcc4,0x3c48bd35,0x3d553d6d,0x3d550000,0x3c483d6d,0xbd7bbd35,0x3d0ebcc4,0xbd0ebd80,0x3d7b3cc4,0xbc483d35,0xbd55bd6d,0xbd550000,0xbc48bd6d,0x3d7b3d35,0xbd0e3cc4,
0x3d550000,0x3c483d6d,0xbd7bbd35,0x3d0ebcc4,0xbd0ebd80,0x3d7b3cc4,0xbc483d35,0xbd55bd6d,0xbd550000,0xbc48bd6d,0x3d7b3d35,0xbd0e3cc4,0x3d0e3d80,0xbd7bbcc4,0x3c48bd35,0x3d553d6d,
0x3d353d80,0xbd350000,0xbd35bd80,0x3d350000,0x3d353d80,0xbd350000,0xbd35bd80,0x3d350000,0x3d353d80,0xbd350000,0xbd35bd80,0x3d350000,0x3d353d80,0xbd350000,0xbd35bd80,0x3d350000,
0xbd350000,0xbd35bd80,0x3d350000,0x3d353d80,0xbd350000,0xbd35bd80,0x3d350000,0x3d353d80,0xbd350000,0xbd35bd80,0x3d350000,0x3d353d80,0xbd350000,0xbd35bd80,0x3d350000,0x3d353d80,
0x3d0e0000,0x3d7b3d6d,0x3c483d35,0xbd55bcc4,0x3d553d80,0xbc483cc4,0xbd7bbd35,0xbd0ebd6d,0xbd0e0000,0xbd7bbd6d,0xbc48bd35,0x3d553cc4,0xbd55bd80,0x3c48bcc4,0x3d7b3d35,0x3d0e3d6d,
0x3d553d80,0xbc483cc4,0xbd7bbd35,0xbd0ebd6d,0xbd0e0000,0xbd7bbd6d,0xbc48bd35,0x3d553cc4,0xbd55bd80,0x3c48bcc4,0x3d7b3d35,0x3d0e3d6d,0x3d0e0000,0x3d7b3d6d,0x3c483d35,0xbd55bcc4,
0x3d6d3d80,0x3cc43d35,0xbcc40000,0xbd6dbd35,0xbd6dbd80,0xbcc4bd35,0x3cc40000,0x3d6d3d35,0x3d6d3d80,0x3cc43d35,0xbcc40000,0xbd6dbd35,0xbd6dbd80,0xbcc4bd35,0x3cc40000,0x3d6d3d35,
0xbcc40000,0xbd6dbd35,0xbd6dbd80,0xbcc4bd35,0x3cc40000,0x3d6d3d35,0x3d6d3d80,0x3cc43d35,0xbcc40000,0xbd6dbd35,0xbd6dbd80,0xbcc4bd35,0x3cc40000,0x3d6d3d35,0x3d6d3d80,0x3cc43d35,
0x3c480000,0x3d0e3cc4,0x3d553d35,0x3d7b3d6d,0xbd7bbd80,0xbd55bd6d,0xbd0ebd35,0xbc48bcc4,0xbc480000,0xbd0ebcc4,0xbd55bd35,0xbd7bbd6d,0x3d7b3d80,0x3d553d6d,0x3d0e3d35,0x3c483cc4,
0x3d7b3d80,0x3d553d6d,0x3d0e3d35,0x3c483cc4,0x3c480000,0x3d0e3cc4,0x3d553d35,0x3d7b3d6d,0xbd7bbd80,0xbd55bd6d,0xbd0ebd35,0xbc48bcc4,0xbc480000,0xbd0ebcc4,0xbd55bd35,0xbd7bbd6d,
0x3000,0x30008000,0x3000,0x30008000,0x3000,0x30008000,0x3000,0x30008000,0x3000,0x30008000,0x3000,0x30008000,0x3000,0x30008000,0x3000,0x30008000,
0x3000,0x30008000,0x30000000,0xb000,0x2a1f2f64,0x2f64aa1f,0x2f64aa1f,0xaa1faf64,0x2da82da8,0x2da8ada8,0x2da8ada8,0xada8ada8,0x2f642a1f,0x2a1faf64,0x2a1faf64,0xaf64aa1f,
0x3000,0x30008000,0xb000,0xb0008000,0x2da82da8,0x2da8ada8,0xada8ada8,0xada82da8,0x30000000,0xb000,0xb0000000,0x3000,0x2da8ada8,0xada8ada8,0xada82da8,0x2da82da8,
0x3000,0x30008000,0xb0000000,0x3000,0x2f642a1f,0x2a1faf64,0xaa1f2f64,0x2f642a1f,0x2da8ada8,0xada8ada8,0x2da82da8,0x2da8ada8,0xaa1faf64,0xaf642a1f,0x2f64aa1f,0xaa1faf64,
0x3000,0x30008000,0x2da82da8,0x2da8ada8,0x263e2fd9,0x2fd9a63e,0x2ea72c72,0x2c72aea7,0x2a1f2f64,0x2f64aa1f,0x2f642a1f,0x2a1faf64,0x2c722ea7,0x2ea7ac72,0x2fd9263e,0x263eafd9,
0x3000,0x30008000,0x2da8ada8,0xada8ada8,0x2c722ea7,0x2ea7ac72,0x263eafd9,0xafd9a63e,0x2f642a1f,0x2a1faf64,0xaa1faf64,0xaf642a1f,0x2fd9a63e,0xa63eafd9,0xaea7ac72,0xac722ea7,
0x3000,0x30008000,0xada8ada8,0xada82da8,0x2ea72c72,0x2c72aea7,0xafd9263e,0x263e2fd9,0x2f64aa1f,0xaa1faf64,0xaa1f2f64,0x2f642a1f,0x263eafd9,0xafd9a63e,0x2c722ea7,0x2ea7ac72,
0x3000,0x30008000,0xada82da8,0x2da82da8,0x2fd9263e,0x263eafd9,0x2c722ea7,0x2ea7ac72,0x2a1faf64,0xaf64aa1f,0x2f64aa1f,0xaa1faf64,0xaea7ac72,0xac722ea7,0xa63eafd9,0xafd9263e,
0x3000,0x30008000,0x3000,0x30008000,0x30000000,0xb000,0x30000000,0xb000,0xb000,0xb0008000,0xb000,0xb0008000,0xb0000000,0x3000,0xb0000000,0x3000,
0x3000,0x30008000,0x30000000,0xb000,0x2f64aa1f,0xaa1faf64,0xaa1faf64,0xaf642a1f,0xada8ada8,0xada82da8,0xada82da8,0x2da82da8,0xaa1f2f64,0x2f642a1f,0x2f642a1f,0x2a1faf64,
0x3000,0x30008000,0xb000,0xb0008000,0x2da8ada8,0xada8ada8,0xada82da8,0x2da82da8,0xb0000000,0x3000,0x30000000,0xb000,0x2da82da8,0x2da8ada8,0xada8ada8,0xada82da8,
0x3000,0x30008000,0xb0000000,0x3000,0x2a1faf64,0xaf64aa1f,0x2f642a1f,0x2a1faf64,0xada82da8,0x2da82da8,0xada8ada8,0xada82da8,0x2f64aa1f,0xaa1faf64,0x2a1f2f64,0x2f64aa1f,
0x3000,0x30008000,0x2da82da8,0x2da8ada8,0x2fd9a63e,0xa63eafd9,0x2c72aea7,0xaea7ac72,0xaa1faf64,0xaf642a1f,0xaf64aa1f,0xaa1f2f64,0xaea72c72,0x2c722ea7,0xa63e2fd9,0x2fd9263e,
0x3000,0x30008000,0x2da8ada8,0xada8ada8,0x2ea7ac72,0xac72aea7,0xafd9a63e,0xa63e2fd9,0xaf64aa1f,0xaa1f2f64,0x2a1f2f64,0x2f64aa1f,0x263e2fd9,0x2fd9a63e,0x2c72aea7,0xaea7ac72,
0x3000,0x30008000,0xada8ada8,0xada82da8,0x2c72aea7,0xaea7ac72,0x263e2fd9,0x2fd9a63e,0xaf642a1f,0x2a1f2f64,0x2a1faf64,0xaf64aa1f,0x2fd9263e,0x263eafd9,0xaea72c72,0x2c722ea7,
0x3000,0x30008000,0xada82da8,0x2da82da8,0x263eafd9,0xafd9a63e,0x2ea7ac72,0xac72aea7,0xaa1f2f64,0x2f642a1f,0xaf642a1f,0x2a1f2f64,0x2c72aea7,0xaea7ac72,0x2fd9a63e,0xa63eafd9,
0x3000,0x30008000,0x3000,0x30008000,0xb000,0xb0008000,0xb000,0xb0008000,0x3000,0x30008000,0x3000,0x30008000,0xb000,0xb0008000,0xb000,0xb0008000,
0x3000,0x30008000,0x30000000,0xb000,0xaa1faf64,0xaf642a1f,0xaf642a1f,0x2a1f2f64,0x2da82da8,0x2da8ada8,0x2da8ada8,0xada8ada8,0xaf64aa1f,0xaa1f2f64,0xaa1f2f64,0x2f642a1f,
0x3000,0x30008000,0xb000,0xb0008000,0xada8ada8,0xada82da8,0x2da82da8,0x2da8ada8,0x30000000,0xb000,0xb0000000,0x3000,0xada82da8,0x2da82da8,0x2da8ada8,0xada8ada8,
0x3000,0x30008000,0xb0000000,0x3000,0xaf64aa1f,0xaa1f2f64,0x2a1faf64,0xaf64aa1f,0x2da8ada8,0xada8ada8,0x2da82da8,0x2da8ada8,0x2a1f2f64,0x2f64aa1f,0xaf642a1f,0x2a1f2f64,
0x3000,0x30008000,0x2da82da8,0x2da8ada8,0xa63eafd9,0xafd9263e,0xaea7ac72,0xac722ea7,0x2a1f2f64,0x2f64aa1f,0x2f642a1f,0x2a1faf64,0xac72aea7,0xaea72c72,0xafd9a63e,0xa63e2fd9,
0x3000,0x30008000,0x2da8ada8,0xada8ada8,0xac72aea7,0xaea72c72,0xa63e2fd9,0x2fd9263e,0x2f642a1f,0x2a1faf64,0xaa1faf64,0xaf642a1f,0xafd9263e,0x263e2fd9,0x2ea72c72,0x2c72aea7,
0x3000,0x30008000,0xada8ada8,0xada82da8,0xaea7ac72,0xac722ea7,0x2fd9a63e,0xa63eafd9,0x2f64aa1f,0xaa1faf64,0xaa1f2f64,0x2f642a1f,0xa63e2fd9,0x2fd9263e,0xac72aea7,0xaea72c72,
0x3000,0x30008000,0xada82da8,0x2da82da8,0xafd9a63e,0xa63e2fd9,0xac72aea7,0xaea72c72,0x2a1faf64,0xaf64aa1f,0x2f64aa1f,0xaa1faf64,0x2ea72c72,0x2c72aea7,0x263e2fd9,0x2fd9a63e,
0x3000,0x30008000,0x3000,0x30008000,0xb0000000,0x3000,0xb0000000,0x3000,0xb000,0xb0008000,0xb000,0xb0008000,0x30000000,0xb000,0x30000000,0xb000,
0x3000,0x30008000,0x30000000,0xb000,0xaf642a1f,0x2a1f2f64,0x2a1f2f64,0x2f64aa1f,0xada8ada8,0xada82da8,0xada82da8,0x2da82da8,0x2a1faf64,0xaf64aa1f,0xaf64aa1f,0xaa1f2f64,
0x3000,0x30008000,0xb000,0xb0008000,0xada82da8,0x2da82da8,0x2da8ada8,0xada8ada8,0xb0000000,0x3000,0x30000000,0xb000,0xada8ada8,0xada82da8,0x2da82da8,0x2da8ada8,
0x3000,0x30008000,0xb0000000,0x3000,0xaa1f2f64,0x2f642a1f,0xaf64aa1f,0xaa1f2f64,0xada82da8,0x2da82da8,0xada8ada8,0xada82da8,0xaf642a1f,0x2a1f2f64,0xaa1faf64,0xaf642a1f,
0x3000,0x30008000,0x2da82da8,0x2da8ada8,0xafd9263e,0x263e2fd9,0xac722ea7,0x2ea72c72,0xaa1faf64,0xaf642a1f,0xaf64aa1f,0xaa1f2f64,0x2ea7ac72,0xac72aea7,0x263eafd9,0xafd9a63e,
0x3000,0x30008000,0x2da8ada8,0xada8ada8,0xaea72c72,0x2c722ea7,0x2fd9263e,0x263eafd9,0xaf64aa1f,0xaa1f2f64,0x2a1f2f64,0x2f64aa1f,0xa63eafd9,0xafd9263e,0xac722ea7,0x2ea72c72,
0x3000,0x30008000,0xada8ada8,0xada82da8,0xac722ea7,0x2ea72c72,0xa63eafd9,0xafd9263e,0xaf642a1f,0x2a1f2f64,0x2a1faf64,0xaf64aa1f,0xafd9a63e,0xa63e2fd9,0x2ea7ac72,0xac72aea7,
0x3000,0x30008000,0xada82da8,0x2da82da8,0xa63e2fd9,0x2fd9263e,0xaea72c72,0x2c722ea7,0xaa1f2f64,0x2f642a1f,0xaf642a1f,0x2a1f2f64,0xac722ea7,0x2ea72c72,0xafd9263e,0x263e2fd9,
0x3000,0x30008000,0x3000,0x30008000,0x3000,0x30008000,0x3000,0x30008000,0x3000,0x30008000,0x3000,0x30008000,0x3000,0x30008000,0x3000,0x30008000,
0xb000,0xb0008000,0xb0000000,0x3000,0xaa1faf64,0xaf642a1f,0xaf642a1f,0x2a1f2f64,0xada8ada8,0xada82da8,0xada82da8,0x2da82da8,0xaf64aa1f,0xaa1f2f64,0xaa1f2f64,0x2f642a1f,
0x3000,0x30008000,0xb000,0xb0008000,0x2da82da8,0x2da8ada8,0xada8ada8,0xada82da8,0x30000000,0xb000,0xb0000000,0x3000,0x2da8ada8,0xada8ada8,0xada82da8,0x2da82da8,
0xb000,0xb0008000,0x30000000,0xb000,0xaf64aa1f,0xaa1f2f64,0x2a1faf64,0xaf64aa1f,0xada82da8,0x2da82da8,0xada8ada8,0xada82da8,0x2a1f2f64,0x2f64aa1f,0xaf642a1f,0x2a1f2f64,
0x30000000,0xb000,0x2da8ada8,0xada8ada8,0x2fd9a63e,0xa63eafd9,0x2c72aea7,0xaea7ac72,0x2f64aa1f,0xaa1faf64,0x2a1faf64,0xaf64aa1f,0x2ea7ac72,0xac72aea7,0x263eafd9,0xafd9a63e,
0xb0000000,0x3000,0x2da82da8,0x2da8ada8,0xaea72c72,0x2c722ea7,0x2fd9263e,0x263eafd9,0xaa1f2f64,0x2f642a1f,0x2f64aa1f,0xaa1faf64,0x263e2fd9,0x2fd9a63e,0x2c72aea7,0xaea7ac72,
0x30000000,0xb000,0xada82da8,0x2da82da8,0x2c72aea7,0xaea7ac72,0x263e2fd9,0x2fd9a63e,0xaa1faf64,0xaf642a1f,0x2f642a1f,0x2a1faf64,0xafd9a63e,0xa63e2fd9,0x2ea7ac72,0xac72aea7,
0xb0000000,0x3000,0xada8ada8,0xada82da8,0xa63e2fd9,0x2fd9263e,0xaea72c72,0x2c722ea7,0x2f642a1f,0x2a1faf64,0x2a1f2f64,0x2f64aa1f,0x2c72aea7,0xaea7ac72,0x2fd9a63e,0xa63eafd9,
0x3000,0x30008000,0x3000,0x30008000,0x30000000,0xb000,0x30000000,0xb000,0xb000,0xb0008000,0xb000,0xb0008000,0xb0000000,0x3000,0xb0000000,0x3000,
0xb000,0xb0008000,0xb0000000,0x3000,0xaf642a1f,0x2a1f2f64,0x2a1f2f64,0x2f64aa1f,0x2da82da8,0x2da8ada8,0x2da8ada8,0xada8ada8,0x2a1faf64,0xaf64aa1f,0xaf64aa1f,0xaa1f2f64,
0x3000,0x30008000,0xb000,0xb0008000,0x2da8ada8,0xada8ada8,0xada82da8,0x2da82da8,0xb0000000,0x3000,0x30000000,0xb000,0x2da82da8,0x2da8ada8,0xada8ada8,0xada82da8,
0xb000,0xb0008000,0x30000000,0xb000,0xaa1f2f64,0x2f642a1f,0xaf64aa1f,0xaa1f2f64,0x2da8ada8,0xada8ada8,0x2da82da8,0x2da8ada8,0xaf642a1f,0x2a1f2f64,0xaa1faf64,0xaf642a1f,
0x30000000,0xb000,0x2da8ada8,0xada8ada8,0xa63eafd9,0xafd9263e,0xaea7ac72,0xac722ea7,0xaf642a1f,0x2a1f2f64,0xaa1f2f64,0x2f642a1f,0x2c722ea7,0x2ea7ac72,0x2fd9263e,0x263eafd9,
0xb0000000,0x3000,0x2da82da8,0x2da8ada8,0x2c722ea7,0x2ea7ac72,0x263eafd9,0xafd9a63e,0x2a1faf64,0xaf64aa1f,0xaf642a1f,0x2a1f2f64,0xafd9263e,0x263e2fd9,0x2ea72c72,0x2c72aea7,
0x30000000,0xb000,0xada82da8,0x2da82da8,0xaea7ac72,0xac722ea7,0x2fd9a63e,0xa63eafd9,0x2a1f2f64,0x2f64aa1f,0xaf64aa1f,0xaa1f2f64,0x263eafd9,0xafd9a63e,0x2c722ea7,0x2ea7ac72,
0xb0000000,0x3000,0xada8ada8,0xada82da8,0x2fd9263e,0x263eafd9,0x2c722ea7,0x2ea7ac72,0xaf64aa1f,0xaa1f2f64,0xaa1faf64,0xaf642a1f,0x2ea72c72,0x2c72aea7,0x263e2fd9,0x2fd9a63e,
0x3000,0x30008000,0x3000,0x30008000,0xb000,0xb0008000,0xb000,0xb0008000,0x3000,0x30008000,0x3000,0x30008000,0xb000,0xb0008000,0xb000,0xb0008000,
0xb000,0xb0008000,0xb0000000,0x3000,0x2a1f2f64,0x2f64aa1f,0x2f64aa1f,0xaa1faf64,0xada8ada8,0xada82da8,0xada82da8,0x2da82da8,0x2f642a1f,0x2a1faf64,0x2a1faf64,0xaf64aa1f,
0x3000,0x30008000,0xb000,0xb0008000,0xada8ada8,0xada82da8,0x2da82da8,0x2da8ada8,0x30000000,0xb000,0xb0000000,0x3000,0xada82da8,0x2da82da8,0x2da8ada8,0xada8ada8,
0xb000,0xb0008000,0x30000000,0xb000,0x2f642a1f,0x2a1faf64,0xaa1f2f64,0x2f642a1f,0xada82da8,0x2da82da8,0xada8ada8,0xada82da8,0xaa1faf64,0xaf642a1f,0x2f64aa1f,0xaa1faf64,
0x30000000,0xb000,0x2da8ada8,0xada8ada8,0xafd9263e,0x263e2fd9,0xac722ea7,0x2ea72c72,0x2f64aa1f,0xaa1faf64,0x2a1faf64,0xaf64aa1f,0xaea72c72,0x2c722ea7,0xa63e2fd9,0x2fd9263e,
0xb0000000,0x3000,0x2da82da8,0x2da8ada8,0x2ea7ac72,0xac72aea7,0xafd9a63e,0xa63e2fd9,0xaa1f2f64,0x2f642a1f,0x2f64aa1f,0xaa1faf64,0xa63eafd9,0xafd9263e,0xac722ea7,0x2ea72c72,
0x30000000,0xb000,0xada82da8,0x2da82da8,0xac722ea7,0x2ea72c72,0xa63eafd9,0xafd9263e,0xaa1faf64,0xaf642a1f,0x2f642a1f,0x2a1faf64,0x2fd9263e,0x263eafd9,0xaea72c72,0x2c722ea7,
0xb0000000,0x3000,0xada8ada8,0xada82da8,0x263eafd9,0xafd9a63e,0x2ea7ac72,0xac72aea7,0x2f642a1f,0x2a1faf64,0x2a1f2f64,0x2f64aa1f,0xac722ea7,0x2ea72c72,0xafd9263e,0x263e2fd9,
0x3000,0x30008000,0x3000,0x30008000,0xb0000000,0x3000,0xb0000000,0x3000,0xb000,0xb0008000,0xb000,0xb0008000,0x30000000,0xb000,0x30000000,0xb000,
0xb000,0xb0008000,0xb0000000,0x3000,0x2f64aa1f,0xaa1faf64,0xaa1faf64,0xaf642a1f,0x2da82da8,0x2da8ada8,0x2da8ada8,0xada8ada8,0xaa1f2f64,0x2f642a1f,0x2f642a1f,0x2a1faf64,
0x3000,0x30008000,0xb000,0xb0008000,0xada82da8,0x2da82da8,0x2da8ada8,0xada8ada8,0xb0000000,0x3000,0x30000000,0xb000,0xada8ada8,0xada82da8,0x2da82da8,0x2da8ada8,
0xb000,0xb0008000,0x30000000,0xb000,0x2a1faf64,0xaf64aa1f,0x2f642a1f,0x2a1faf64,0x2da8ada8,0xada8ada8,0x2da82da8,0x2da8ada8,0x2f64aa1f,0xaa1faf64,0x2a1f2f64,0x2f64aa1f,
0x30000000,0xb000,0x2da8ada8,0xada8ada8,0x263e2fd9,0x2fd9a63e,0x2ea72c72,0x2c72aea7,0xaf642a1f,0x2a1f2f64,0xaa1f2f64,0x2f642a1f,0xac72aea7,0xaea72c72,0xafd9a63e,0xa63e2fd9,
0xb0000000,0x3000,0x2da82da8,0x2da8ada8,0xac72aea7,0xaea72c72,0xa63e2fd9,0x2fd9263e,0x2a1faf64,0xaf64aa1f,0xaf642a1f,0x2a1f2f64,0x2fd9a63e,0xa63eafd9,0xaea7ac72,0xac722ea7,
0x30000000,0xb000,0xada82da8,0x2da82da8,0x2ea72c72,0x2c72aea7,0xafd9263e,0x263e2fd9,0x2a1f2f64,0x2f64aa1f,0xaf64aa1f,0xaa1f2f64,0xa63e2fd9,0x2fd9263e,0xac72aea7,0xaea72c72,
0xb0000000,0x3000,0xada8ada8,0xada82da8,0xafd9a63e,0xa63e2fd9,0xac72aea7,0xaea72c72,0xaf64aa1f,0xaa1f2f64,0xaa1faf64,0xaf642a1f,0xaea7ac72,0xac722ea7,0xa63eafd9,0xafd9263e,
0x3000,0x30008000,0x3000,0x30008000,0x3000,0x30008000,0x3000,0x30008000,0x3000,0x30008000,0x3000,0x30008000,0x3000,0x30008000,0x3000,0x30008000,
0x3000,0x30008000,0x30000000,0xb000,0x2a1f2f64,0x2f64aa1f,0x2f64aa1f,0xaa1faf64,0x2da82da8,0x2da8ada8,0x2da8ada8,0xada8ada8,0x2f642a1f,0x2a1faf64,0x2a1faf64,0xaf64aa1f,
0x3000,0x30008000,0xb000,0xb0008000,0x2da82da8,0x2da8ada8,0xada8ada8,0xada82da8,0x30000000,0xb000,0xb0000000,0x3000,0x2da8ada8,0xada8ada8,0xada82da8,0x2da82da8,
0x3000,0x30008000,0xb0000000,0x3000,0x2f642a1f,0x2a1faf64,0xaa1f2f64,0x2f642a1f,0x2da8ada8,0xada8ada8,0x2da82da8,0x2da8ada8,0xaa1faf64,0xaf642a1f,0x2f64aa1f,0xaa1faf64,
0xb000,0xb0008000,0xada8ada8,0xada82da8,0xa63eafd9,0xafd9263e,0xaea7ac72,0xac722ea7,0xaa1faf64,0xaf642a1f,0xaf64aa1f,0xaa1f2f64,0xac72aea7,0xaea72c72,0xafd9a63e,0xa63e2fd9,
0xb000,0xb0008000,0xada82da8,0x2da82da8,0xac72aea7,0xaea72c72,0xa63e2fd9,0x2fd9263e,0xaf64aa1f,0xaa1f2f64,0x2a1f2f64,0x2f64aa1f,0xafd9263e,0x263e2fd9,0x2ea72c72,0x2c72aea7,
0xb000,0xb0008000,0x2da82da8,0x2da8ada8,0xaea7ac72,0xac722ea7,0x2fd9a63e,0xa63eafd9,0xaf642a1f,0x2a1f2f64,0x2a1faf64,0xaf64aa1f,0xa63e2fd9,0x2fd9263e,0xac72aea7,0xaea72c72,
0xb000,0xb0008000,0x2da8ada8,0xada8ada8,0xafd9a63e,0xa63e2fd9,0xac72aea7,0xaea72c72,0xaa1f2f64,0x2f642a1f,0xaf642a1f,0x2a1f2f64,0x2ea72c72,0x2c72aea7,0x263e2fd9,0x2fd9a63e,
0x3000,0x30008000,0x3000,0x30008000,0x30000000,0xb000,0x30000000,0xb000,0xb000,0xb0008000,0xb000,0xb0008000,0xb0000000,0x3000,0xb0000000,0x3000,
0x3000,0x30008000,0x30000000,0xb000,0x2f64aa1f,0xaa1faf64,0xaa1faf64,0xaf642a1f,0xada8ada8,0xada82da8,0xada82da8,0x2da82da8,0xaa1f2f64,0x2f642a1f,0x2f642a1f,0x2a1faf64,
0x3000,0x30008000,0xb000,0xb0008000,0x2da8ada8,0xada8ada8,0xada82da8,0x2da82da8,0xb0000000,0x3000,0x30000000,0xb000,0x2da82da8,0x2da8ada8,0xada8ada8,0xada82da8,
0x3000,0x30008000,0xb0000000,0x3000,0x2a1faf64,0xaf64aa1f,0x2f642a1f,0x2a1faf64,0xada82da8,0x2da82da8,0xada8ada8,0xada82da8,0x2f64aa1f,0xaa1faf64,0x2a1f2f64,0x2f64aa1f,
0xb000,0xb0008000,0xada8ada8,0xada82da8,0xafd9263e,0x263e2fd9,0xac722ea7,0x2ea72c72,0x2a1f2f64,0x2f64aa1f,0x2f642a1f,0x2a1faf64,0x2ea7ac72,0xac72aea7,0x263eafd9,0xafd9a63e,
0xb000,0xb0008000,0xada82da8,0x2da82da8,0xaea72c72,0x2c722ea7,0x2fd9263e,0x263eafd9,0x2f642a1f,0x2a1faf64,0xaa1faf64,0xaf642a1f,0xa63eafd9,0xafd9263e,0xac722ea7,0x2ea72c72,
0xb000,0xb0008000,0x2da82da8,0x2da8ada8,0xac722ea7,0x2ea72c72,0xa63eafd9,0xafd9263e,0x2f64aa1f,0xaa1faf64,0xaa1f2f64,0x2f642a1f,0xafd9a63e,0xa63e2fd9,0x2ea7ac72,0xac72aea7,
0xb000,0xb0008000,0x2da8ada8,0xada8ada8,0xa63e2fd9,0x2fd9263e,0xaea72c72,0x2c722ea7,0x2a1faf64,0xaf64aa1f,0x2f64aa1f,0xaa1faf64,0xac722ea7,0x2ea72c72,0xafd9263e,0x263e2fd9,
0x3000,0x30008000,0x3000,0x30008000,0xb000,0xb0008000,0xb000,0xb0008000,0x3000,0x30008000,0x3000,0x30008000,0xb000,0xb0008000,0xb000,0xb0008000,
0x3000,0x30008000,0x30000000,0xb000,0xaa1faf64,0xaf642a1f,0xaf642a1f,0x2a1f2f64,0x2da82da8,0x2da8ada8,0x2da8ada8,0xada8ada8,0xaf64aa1f,0xaa1f2f64,0xaa1f2f64,0x2f642a1f,
0x3000,0x30008000,0xb000,0xb0008000,0xada8ada8,0xada82da8,0x2da82da8,0x2da8ada8,0x30000000,0xb000,0xb0000000,0x3000,0xada82da8,0x2da82da8,0x2da8ada8,0xada8ada8,
0x3000,0x30008000,0xb0000000,0x3000,0xaf64aa1f,0xaa1f2f64,0x2a1faf64,0xaf64aa1f,0x2da8ada8,0xada8ada8,0x2da82da8,0x2da8ada8,0x2a1f2f64,0x2f64aa1f,0xaf642a1f,0x2a1f2f64,
0xb000,0xb0008000,0xada8ada8,0xada82da8,0x263e2fd9,0x2fd9a63e,0x2ea72c72,0x2c72aea7,0xaa1faf64,0xaf642a1f,0xaf64aa1f,0xaa1f2f64,0x2c722ea7,0x2ea7ac72,0x2fd9263e,0x263eafd9,
0xb000,0xb0008000,0xada82da8,0x2da82da8,0x2c722ea7,0x2ea7ac72,0x263eafd9,0xafd9a63e,0xaf64aa1f,0xaa1f2f64,0x2a1f2f64,0x2f64aa1f,0x2fd9a63e,0xa63eafd9,0xaea7ac72,0xac722ea7,
0xb000,0xb0008000,0x2da82da8,0x2da8ada8,0x2ea72c72,0x2c72aea7,0xafd9263e,0x263e2fd9,0xaf642a1f,0x2a1f2f64,0x2a1faf64,0xaf64aa1f,0x263eafd9,0xafd9a63e,0x2c722ea7,0x2ea7ac72,
0xb000,0xb0008000,0x2da8ada8,0xada8ada8,0x2fd9263e,0x263eafd9,0x2c722ea7,0x2ea7ac72,0xaa1f2f64,0x2f642a1f,0xaf642a1f,0x2a1f2f64,0xaea7ac72,0xac722ea7,0xa63eafd9,0xafd9263e,
0x3000,0x30008000,0x3000,0x30008000,0xb0000000,0x3000,0xb0000000,0x3000,0xb000,0xb0008000,0xb000,0xb0008000,0x30000000,0xb000,0x30000000,0xb000,
0x3000,0x30008000,0x30000000,0xb000,0xaf642a1f,0x2a1f2f64,0x2a1f2f64,0x2f64aa1f,0xada8ada8,0xada82da8,0xada82da8,0x2da82da8,0x2a1faf64,0xaf64aa1f,0xaf64aa1f,0xaa1f2f64,
0x3000,0x30008000,0xb000,0xb0008000,0xada82da8,0x2da82da8,0x2da8ada8,0xada8ada8,0xb0000000,0x3000,0x30000000,0xb000,0xada8ada8,0xada82da8,0x2da82da8,0x2da8ada8,
0x3000,0x30008000,0xb0000000,0x3000,0xaa1f2f64,0x2f642a1f,0xaf64aa1f,0xaa1f2f64,0xada82da8,0x2da82da8,0xada8ada8,0xada82da8,0xaf642a1f,0x2a1f2f64,0xaa1faf64,0xaf642a1f,
0xb000,0xb0008000,0xada8ada8,0xada82da8,0x2fd9a63e,0xa63eafd9,0x2c72aea7,0xaea7ac72,0x2a1f2f64,0x2f64aa1f,0x2f642a1f,0x2a1faf64,0xaea72c72,0x2c722ea7,0xa63e2fd9,0x2fd9263e,
0xb000,0xb0008000,0xada82da8,0x2da82da8,0x2ea7ac72,0xac72aea7,0xafd9a63e,0xa63e2fd9,0x2f642a1f,0x2a1faf64,0xaa1faf64,0xaf642a1f,0x263e2fd9,0x2fd9a63e,0x2c72aea7,0xaea7ac72,
0xb000,0xb0008000,0x2da82da8,0x2da8ada8,0x2c72aea7,0xaea7ac72,0x263e2fd9,0x2fd9a63e,0x2f64aa1f,0xaa1faf64,0xaa1f2f64,0x2f642a1f,0x2fd9263e,0x263eafd9,0xaea72c72,0x2c722ea7,
0xb000,0xb0008000,0x2da8ada8,0xada8ada8,0x263eafd9,0xafd9a63e,0x2ea7ac72,0xac72aea7,0x2a1faf64,0xaf64aa1f,0x2f64aa1f,0xaa1faf64,0x2c72aea7,0xaea7ac72,0x2fd9a63e,0xa63eafd9,
0x3000,0x30008000,0x3000,0x30008000,0x3000,0x30008000,0x3000,0x30008000,0x3000,0x30008000,0x3000,0x30008000,0x3000,0x30008000,0x3000,0x30008000,
0xb000,0xb0008000,0xb0000000,0x3000,0xaa1faf64,0xaf642a1f,0xaf642a1f,0x2a1f2f64,0xada8ada8,0xada82da8,0xada82da8,0x2da82da8,0xaf64aa1f,0xaa1f2f64,0xaa1f2f64,0x2f642a1f,
0x3000,0x30008000,0xb000,0xb0008000,0x2da82da8,0x2da8ada8,0xada8ada8,0xada82da8,0x30000000,0xb000,0xb0000000,0x3000,0x2da8ada8,0xada8ada8,0xada82da8,0x2da82da8,
0xb000,0xb0008000,0x30000000,0xb000,0xaf64aa1f,0xaa1f2f64,0x2a1faf64,0xaf64aa1f,0xada82da8,0x2da82da8,0xada8ada8,0xada82da8,0x2a1f2f64,0x2f64aa1f,0xaf642a1f,0x2a1f2f64,
0xb0000000,0x3000,0xada82da8,0x2da82da8,0xafd9263e,0x263e2fd9,0xac722ea7,0x2ea72c72,0xaf642a1f,0x2a1f2f64,0xaa1f2f64,0x2f642a1f,0xaea72c72,0x2c722ea7,0xa63e2fd9,0x2fd9263e,
0x30000000,0xb000,0xada8ada8,0xada82da8,0x2ea7ac72,0xac72aea7,0xafd9a63e,0xa63e2fd9,0x2a1faf64,0xaf64aa1f,0xaf642a1f,0x2a1f2f64,0xa63eafd9,0xafd9263e,0xac722ea7,0x2ea72c72,
0xb0000000,0x3000,0x2da8ada8,0xada8ada8,0xac722ea7,0x2ea72c72,0xa63eafd9,0xafd9263e,0x2a1f2f64,0x2f64aa1f,0xaf64aa1f,0xaa1f2f64,0x2fd9263e,0x263eafd9,0xaea72c72,0x2c722ea7,
0x30000000,0xb000,0x2da82da8,0x2da8ada8,0x263eafd9,0xafd9a63e,0x2ea7ac72,0xac72aea7,0xaf64aa1f,0xaa1f2f64,0xaa1faf64,0xaf642a1f,0xac722ea7,0x2ea72c72,0xafd9263e,0x263e2fd9,
0x3000,0x30008000,0x3000,0x30008000,0x30000000,0xb000,0x30000000,0xb000,0xb000,0xb0008000,0xb000,0xb0008000,0xb0000000,0x3000,0xb0000000,0x3000,
0xb000,0xb0008000,0xb0000000,0x3000,0xaf642a1f,0x2a1f2f64,0x2a1f2f64,0x2f64aa1f,0x2da82da8,0x2da8ada8,0x2da8ada8,0xada8ada8,0x2a1faf64,0xaf64aa1f,0xaf64aa1f,0xaa1f2f64,
0x3000,0x30008000,0xb000,0xb0008000,0x2da8ada8,0xada8ada8,0xada82da8,0x2da82da8,0xb0000000,0x3000,0x30000000,0xb000,0x2da82da8,0x2da8ada8,0xada8ada8,0xada82da8,
0xb000,0xb0008000,0x30000000,0xb000,0xaa1f2f64,0x2f642a1f,0xaf64aa1f,0xaa1f2f64,0x2da8ada8,0xada8ada8,0x2da82da8,0x2da8ada8,0xaf642a1f,0x2a1f2f64,0xaa1faf64,0xaf642a1f,
0xb0000000,0x3000,0xada82da8,0x2da82da8,0x263e2fd9,0x2fd9a63e,0x2ea72c72,0x2c72aea7,0x2f64aa1f,0xaa1faf64,0x2a1faf64,0xaf64aa1f,0xac72aea7,0xaea72c72,0xafd9a63e,0xa63e2fd9,
0x30000000,0xb000,0xada8ada8,0xada82da8,0xac72aea7,0xaea72c72,0xa63e2fd9,0x2fd9263e,0xaa1f2f64,0x2f642a1f,0x2f64aa1f,0xaa1faf64,0x2fd9a63e,0xa63eafd9,0xaea7ac72,0xac722ea7,
0xb0000000,0x3000,0x2da8ada8,0xada8ada8,0x2ea72c72,0x2c72aea7,0xafd9263e,0x263e2fd9,0xaa1faf64,0xaf642a1f,0x2f642a1f,0x2a1faf64,0xa63e2fd9,0x2fd9263e,0xac72aea7,0xaea72c72,
0x30000000,0xb000,0x2da82da8,0x2da8ada8,0xafd9a63e,0xa63e2fd9,0xac72aea7,0xaea72c72,0x2f642a1f,0x2a1faf64,0x2a1f2f64,0x2f64aa1f,0xaea7ac72,0xac722ea7,0xa63eafd9,0xafd9263e,
0x3000,0x30008000,0x3000,0x30008000,0xb000,0xb0008000,0xb000,0xb0008000,0x3000,0x30008000,0x3000,0x30008000,0xb000,0xb0008000,0xb000,0xb0008000,
0xb000,0xb0008000,0xb0000000,0x3000,0x2a1f2f64,0x2f64aa1f,0x2f64aa1f,0xaa1faf64,0xada8ada8,0xada82da8,0xada82da8,0x2da82da8,0x2f642a1f,0x2a1faf64,0x2a1faf64,0xaf64aa1f,
0x3000,0x30008000,0xb000,0xb0008000,0xada8ada8,0xada82da8,0x2da82da8,0x2da8ada8,0x30000000,0xb000,0xb0000000,0x3000,0xada82da8,0x2da82da8,0x2da8ada8,0xada8ada8,
0xb000,0xb0008000,0x30000000,0xb000,0x2f642a1f,0x2a1faf64,0xaa1f2f64,0x2f642a1f,0xada82da8,0x2da82da8,0xada8ada8,0xada82da8,0xaa1faf64,0xaf642a1f,0x2f64aa1f,0xaa1faf64,
0xb0000000,0x3000,0xada82da8,0x2da82da8,0x2fd9a63e,0xa63eafd9,0x2c72aea7,0xaea7ac72,0xaf642a1f,0x2a1f2f64,0xaa1f2f64,0x2f642a1f,0x2ea7ac72,0xac72aea7,0x263eafd9,0xafd9a63e,
0x30000000,0xb000,0xada8ada8,0xada82da8,0xaea72c72,0x2c722ea7,0x2fd9263e,0x263eafd9,0x2a1faf64,0xaf64aa1f,0xaf642a1f,0x2a1f2f64,0x263e2fd9,0x2fd9a63e,0x2c72aea7,0xaea7ac72,
0xb0000000,0x3000,0x2da8ada8,0xada8ada8,0x2c72aea7,0xaea7ac72,0x263e2fd9,0x2fd9a63e,0x2a1f2f64,0x2f64aa1f,0xaf64aa1f,0xaa1f2f64,0xafd9a63e,0xa63e2fd9,0x2ea7ac72,0xac72aea7,
0x30000000,0xb000,0x2da82da8,0x2da8ada8,0xa63e2fd9,0x2fd9263e,0xaea72c72,0x2c722ea7,0xaf64aa1f,0xaa1f2f64,0xaa1faf64,0xaf642a1f,0x2c72aea7,0xaea7ac72,0x2fd9a63e,0xa63eafd9,
0x3000,0x30008000,0x3000,0x30008000,0xb0000000,0x3000,0xb0000000,0x3000,0xb000,0xb0008000,0xb000,0xb0008000,0x30000000,0xb000,0x30000000,0xb000,
0xb000,0xb0008000,0xb0000000,0x3000,0x2f64aa1f,0xaa1faf64,0xaa1faf64,0xaf642a1f,0x2da82da8,0x2da8ada8,0x2da8ada8,0xada8ada8,0xaa1f2f64,0x2f642a1f,0x2f642a1f,0x2a1faf64,
0x3000,0x30008000,0xb000,0xb0008000,0xada82da8,0x2da82da8,0x2da8ada8,0xada8ada8,0xb0000000,0x3000,0x30000000,0xb000,0xada8ada8,0xada82da8,0x2da82da8,0x2da8ada8,
0xb000,0xb0008000,0x30000000,0xb000,0x2a1faf64,0xaf64aa1f,0x2f642a1f,0x2a1faf64,0x2da8ada8,0xada8ada8,0x2da82da8,0x2da8ada8,0x2f64aa1f,0xaa1faf64,0x2a1f2f64,0x2f64aa1f,
0xb0000000,0x3000,0xada82da8,0x2da82da8,0xa63eafd9,0xafd9263e,0xaea7ac72,0xac722ea7,0x2f64aa1f,0xaa1faf64,0x2a1faf64,0xaf64aa1f,0x2c722ea7,0x2ea7ac72,0x2fd9263e,0x263eafd9,
0x30000000,0xb000,0xada8ada8,0xada82da8,0x2c722ea7,0x2ea7ac72,0x263eafd9,0xafd9a63e,0xaa1f2f64,0x2f642a1f,0x2f64aa1f,0xaa1faf64,0xafd9263e,0x263e2fd9,0x2ea72c72,0x2c72aea7,
0xb0000000,0x3000,0x2da8ada8,0xada8ada8,0xaea7ac72,0xac722ea7,0x2fd9a63e,0xa63eafd9,0xaa1faf64,0xaf642a1f,0x2f642a1f,0x2a1faf64,0x263eafd9,0xafd9a63e,0x2c722ea7,0x2ea7ac72,
0x30000000,0xb000,0x2da82da8,0x2da8ada8,0x2fd9263e,0x263eafd9,0x2c722ea7,0x2ea7ac72,0x2f642a1f,0x2a1faf64,0x2a1f2f64,0x2f64aa1f,0x2ea72c72,0x2c72aea7,0x263e2fd9,0x2fd9a63e,
0x3000,0x30008000,0x3000,0x30008000,0x3000,0x30008000,0x3000,0x30008000,0x3000,0x30008000,0x3000,0x30008000,0x3000,0x30008000,0x3000,0x30008000,
0x263e2fd9,0x2fd9a63e,0x2fd9a63e,0xa63eafd9,0x2c722ea7,0x2ea7ac72,0x2ea7ac72,0xac72aea7,0x2ea72c72,0x2c72aea7,0x2c72aea7,0xaea7ac72,0x2fd9263e,0x263eafd9,0x263eafd9,0xafd9a63e,
0x2a1f2f64,0x2f64aa1f,0xaa1faf64,0xaf642a1f,0x2f642a1f,0x2a1faf64,0xaf64aa1f,0xaa1f2f64,0x2f64aa1f,0xaa1faf64,0xaf642a1f,0x2a1f2f64,0x2a1faf64,0xaf64aa1f,0xaa1f2f64,0x2f642a1f,
0x2c722ea7,0x2ea7ac72,0xaea72c72,0x2c722ea7,0x2fd9a63e,0xa63eafd9,0x263e2fd9,0x2fd9a63e,0x263eafd9,0xafd9a63e,0x2fd9263e,0x263eafd9,0xaea7ac72,0xac722ea7,0x2c72aea7,0xaea7ac72,
0x22462ff6,0x2ff6a246,0x2e2f2d13,0x2d13ae2f,0x28a52fa8,0x2fa8a8a5,0x2f0e2b8b,0x2b8baf0e,0x2b8b2f0e,0x2f0eab8b,0x2fa828a5,0x28a5afa8,0x2d132e2f,0x2e2fad13,0x2ff62246,0x2246aff6,
0x28a52fa8,0x2fa8a8a5,0x2b8baf0e,0xaf0eab8b,0x2e2f2d13,0x2d13ae2f,0xa246aff6,0xaff62246,0x2ff62246,0x2246aff6,0xad13ae2f,0xae2f2d13,0x2f0eab8b,0xab8baf0e,0xafa8a8a5,0xa8a52fa8,
0x2b8b2f0e,0x2f0eab8b,0xafa8a8a5,0xa8a52fa8,0x2ff62246,0x2246aff6,0xae2f2d13,0x2d132e2f,0x2d13ae2f,0xae2fad13,0x22462ff6,0x2ff6a246,0xa8a5afa8,0xafa828a5,0x2f0e2b8b,0x2b8baf0e,
0x2d132e2f,0x2e2fad13,0xa2462ff6,0x2ff62246,0x2f0eab8b,0xab8baf0e,0x2fa828a5,0x28a5afa8,0xa8a5afa8,0xafa828a5,0x2b8baf0e,0xaf0eab8b,0xaff62246,0x22462ff6,0xae2fad13,0xad132e2f,
0x2da82da8,0x2da8ada8,0x2da82da8,0x2da8ada8,0x2da8ada8,0xada8ada8,0x2da8ada8,0xada8ada8,0xada8ada8,0xada82da8,0xada8ada8,0xada82da8,0xada82da8,0x2da82da8,0xada82da8,0x2da82da8,
0x2ea72c72,0x2c72aea7,0x2c72aea7,0xaea7ac72,0x263eafd9,0xafd9a63e,0xafd9a63e,0xa63e2fd9,0xafd9263e,0x263e2fd9,0x263e2fd9,0x2fd9a63e,0x2c722ea7,0x2ea7ac72,0x2ea7ac72,0xac72aea7,
0x2f642a1f,0x2a1faf64,0xaf64aa1f,0xaa1f2f64,0xaa1faf64,0xaf642a1f,0x2a1f2f64,0x2f64aa1f,0xaa1f2f64,0x2f642a1f,0x2a1faf64,0xaf64aa1f,0x2f64aa1f,0xaa1faf64,0xaf642a1f,0x2a1f2f64,
0x2fd9263e,0x263eafd9,0xa63e2fd9,0x2fd9263e,0xaea7ac72,0xac722ea7,0x2c72aea7,0xaea7ac72,0x2c722ea7,0x2ea7ac72,0xaea72c72,0x2c722ea7,0xa63eafd9,0xafd9263e,0x2fd9a63e,0xa63eafd9,
0x2e2f2d13,0x2d13ae2f,0x2ff6a246,0xa246aff6,0x2b8baf0e,0xaf0eab8b,0xa8a5afa8,0xafa828a5,0xafa8a8a5,0xa8a52fa8,0xaf0e2b8b,0x2b8b2f0e,0xa2462ff6,0x2ff62246,0x2d132e2f,0x2e2fad13,
0x2f0e2b8b,0x2b8baf0e,0xa8a5afa8,0xafa828a5,0xa246aff6,0xaff62246,0xad132e2f,0x2e2f2d13,0xae2f2d13,0x2d132e2f,0x2ff62246,0x2246aff6,0x2fa828a5,0x28a5afa8,0xab8baf0e,0xaf0e2b8b,
0x2fa828a5,0x28a5afa8,0xaf0e2b8b,0x2b8b2f0e,0xad13ae2f,0xae2f2d13,0x2ff62246,0x2246aff6,0x22462ff6,0x2ff6a246,0xae2fad13,0xad132e2f,0x2b8baf0e,0xaf0eab8b,0x28a52fa8,0x2fa8a8a5,
0x2ff62246,0x2246aff6,0x2d132e2f,0x2e2fad13,0xafa8a8a5,0xa8a52fa8,0xab8baf0e,0xaf0e2b8b,0x2f0e2b8b,0x2b8baf0e,0x28a52fa8,0x2fa8a8a5,0xae2fad13,0xad132e2f,0xa246aff6,0xaff62246,
0x30000000,0xb000,0x30000000,0xb000,0xb0000000,0x3000,0xb0000000,0x3000,0x30000000,0xb000,0x30000000,0xb000,0xb0000000,0x3000,0xb0000000,0x3000,
0x2fd9a63e,0xa63eafd9,0xa63eafd9,0xafd9263e,0xaea72c72,0x2c722ea7,0x2c722ea7,0x2ea7ac72,0x2c72aea7,0xaea7ac72,0xaea7ac72,0xac722ea7,0xa63e2fd9,0x2fd9263e,0x2fd9263e,0x263eafd9,
0x2f64aa1f,0xaa1faf64,0xaf642a1f,0x2a1f2f64,0xaa1f2f64,0x2f642a1f,0x2a1faf64,0xaf64aa1f,0xaa1faf64,0xaf642a1f,0x2a1f2f64,0x2f64aa1f,0x2f642a1f,0x2a1faf64,0xaf64aa1f,0xaa1f2f64,
0x2ea7ac72,0xac72aea7,0x2c722ea7,0x2ea7ac72,0x263e2fd9,0x2fd9a63e,0xafd9263e,0x263e2fd9,0xafd9a63e,0xa63e2fd9,0x263eafd9,0xafd9a63e,0x2c72aea7,0xaea7ac72,0x2ea72c72,0x2c72aea7,
0x2ff6a246,0xa246aff6,0x2d13ae2f,0xae2fad13,0xafa828a5,0x28a52fa8,0xab8b2f0e,0x2f0e2b8b,0x2f0eab8b,0xab8baf0e,0x28a5afa8,0xafa8a8a5,0xae2f2d13,0x2d132e2f,0xa2462ff6,0x2ff62246,
0x2fa8a8a5,0xa8a5afa8,0xaf0eab8b,0xab8b2f0e,0xad132e2f,0x2e2f2d13,0x2ff6a246,0xa246aff6,0x2246aff6,0xaff6a246,0xae2f2d13,0x2d132e2f,0x2b8b2f0e,0x2f0eab8b,0x28a5afa8,0xafa8a8a5,
0x2f0eab8b,0xab8baf0e,0xa8a52fa8,0x2fa828a5,0xa2462ff6,0x2ff62246,0xad13ae2f,0xae2f2d13,0xae2fad13,0xad132e2f,0x2ff6a246,0xa246aff6,0x2fa8a8a5,0xa8a5afa8,0xab8b2f0e,0x2f0e2b8b,
0x2e2fad13,0xad13ae2f,0x2ff62246,0x2246aff6,0x2b8b2f0e,0x2f0eab8b,0xa8a52fa8,0x2fa828a5,0xafa828a5,0x28a52fa8,0xaf0eab8b,0xab8b2f0e,0xa246aff6,0xaff62246,0x2d13ae2f,0xae2fad13,
0x2da8ada8,0xada8ada8,0x2da8ada8,0xada8ada8,0x2da82da8,0x2da8ada8,0x2da82da8,0x2da8ada8,0xada82da8,0x2da82da8,0xada82da8,0x2da82da8,0xada8ada8,0xada82da8,0xada8ada8,0xada82da8,
0x2c72aea7,0xaea7ac72,0xaea7ac72,0xac722ea7,0x2fd9263e,0x263eafd9,0x263eafd9,0xafd9a63e,0x263e2fd9,0x2fd9a63e,0x2fd9a63e,0xa63eafd9,0xaea72c72,0x2c722ea7,0x2c722ea7,0x2ea7ac72,
0x2a1faf64,0xaf64aa1f,0xaa1f2f64,0x2f642a1f,0x2f64aa1f,0xaa1faf64,0xaf642a1f,0x2a1f2f64,0x2f642a1f,0x2a1faf64,0xaf64aa1f,0xaa1f2f64,0x2a1f2f64,0x2f64aa1f,0xaa1faf64,0xaf642a1f,
0x263eafd9,0xafd9a63e,0x2fd9263e,0x263eafd9,0x2c72aea7,0xaea7ac72,0x2ea72c72,0x2c72aea7,0x2ea7ac72,0xac72aea7,0x2c722ea7,0x2ea7ac72,0x2fd9a63e,0xa63eafd9,0x263e2fd9,0x2fd9a63e,
0x2d13ae2f,0xae2fad13,0xa246aff6,0xaff62246,0x2f0e2b8b,0x2b8baf0e,0x2fa8a8a5,0xa8a5afa8,0xa8a52fa8,0x2fa828a5,0x2b8b2f0e,0x2f0eab8b,0xaff6a246,0xa2462ff6,0xae2f2d13,0x2d132e2f,
0x2b8baf0e,0xaf0eab8b,0xafa828a5,0x28a52fa8,0x2ff6a246,0xa246aff6,0xae2fad13,0xad132e2f,0x2d132e2f,0x2e2fad13,0x2246aff6,0xaff6a246,0xa8a52fa8,0x2fa828a5,0x2f0eab8b,0xab8baf0e,
0x28a5afa8,0xafa8a8a5,0x2b8b2f0e,0x2f0eab8b,0x2e2fad13,0xad13ae2f,0xa2462ff6,0x2ff62246,0x2ff6a246,0xa246aff6,0xad132e2f,0x2e2f2d13,0x2f0e2b8b,0x2b8baf0e,0xafa828a5,0x28a52fa8,
0x2246aff6,0xaff6a246,0x2e2fad13,0xad13ae2f,0x28a5afa8,0xafa8a8a5,0x2f0eab8b,0xab8baf0e,0x2b8baf0e,0xaf0eab8b,0x2fa8a8a5,0xa8a5afa8,0x2d13ae2f,0xae2fad13,0x2ff6a246,0xa246aff6,
0x3000,0x30008000,0x3000,0x30008000,0x3000,0x30008000,0x3000,0x30008000,0x3000,0x30008000,0x3000,0x30008000,0x3000,0x30008000,0x3000,0x30008000,
0xa63eafd9,0xafd9263e,0xafd9263e,0x263e2fd9,0xac72aea7,0xaea72c72,0xaea72c72,0x2c722ea7,0xaea7ac72,0xac722ea7,0xac722ea7,0x2ea72c72,0xafd9a63e,0xa63e2fd9,0xa63e2fd9,0x2fd9263e,
0x2a1f2f64,0x2f64aa1f,0xaa1faf64,0xaf642a1f,0x2f642a1f,0x2a1faf64,0xaf64aa1f,0xaa1f2f64,0x2f64aa1f,0xaa1faf64,0xaf642a1f,0x2a1f2f64,0x2a1faf64,0xaf64aa1f,0xaa1f2f64,0x2f642a1f,
0xac72aea7,0xaea72c72,0x2ea7ac72,0xac72aea7,0xafd9263e,0x263e2fd9,0xa63eafd9,0xafd9263e,0xa63e2fd9,0x2fd9263e,0xafd9a63e,0xa63e2fd9,0x2ea72c72,0x2c72aea7,0xac722ea7,0x2ea72c72,
0x2ff6a246,0xa246aff6,0x2d13ae2f,0xae2fad13,0x2fa8a8a5,0xa8a5afa8,0x2b8baf0e,0xaf0eab8b,0x2f0eab8b,0xab8baf0e,0x28a5afa8,0xafa8a8a5,0x2e2fad13,0xad13ae2f,0x2246aff6,0xaff6a246,
0xafa828a5,0x28a52fa8,0x2f0e2b8b,0x2b8baf0e,0xad132e2f,0x2e2f2d13,0x2ff6a246,0xa246aff6,0xa2462ff6,0x2ff62246,0x2e2fad13,0xad13ae2f,0x2b8b2f0e,0x2f0eab8b,0x28a5afa8,0xafa8a8a5,
0x2f0eab8b,0xab8baf0e,0xa8a52fa8,0x2fa828a5,0x2246aff6,0xaff6a246,0x2d132e2f,0x2e2fad13,0xae2fad13,0xad132e2f,0x2ff6a246,0xa246aff6,0xafa828a5,0x28a52fa8,0x2b8baf0e,0xaf0eab8b,
0xae2f2d13,0x2d132e2f,0xaff6a246,0xa2462ff6,0x2b8b2f0e,0x2f0eab8b,0xa8a52fa8,0x2fa828a5,0x2fa8a8a5,0xa8a5afa8,0x2f0e2b8b,0x2b8baf0e,0xa246aff6,0xaff62246,0x2d13ae2f,0xae2fad13,
0x2da82da8,0x2da8ada8,0x2da82da8,0x2da8ada8,0x2da8ada8,0xada8ada8,0x2da8ada8,0xada8ada8,0xada8ada8,0xada82da8,0xada8ada8,0xada82da8,0xada82da8,0x2da82da8,0xada82da8,0x2da82da8,
0xaea7ac72,0xac722ea7,0xac722ea7,0x2ea72c72,0xa63e2fd9,0x2fd9263e,0x2fd9263e,0x263eafd9,0x2fd9a63e,0xa63eafd9,0xa63eafd9,0xafd9263e,0xac72aea7,0xaea72c72,0xaea72c72,0x2c722ea7,
0x2f642a1f,0x2a1faf64,0xaf64aa1f,0xaa1f2f64,0xaa1faf64,0xaf642a1f,0x2a1f2f64,0x2f64aa1f,0xaa1f2f64,0x2f642a1f,0x2a1faf64,0xaf64aa1f,0x2f64aa1f,0xaa1faf64,0xaf642a1f,0x2a1f2f64,
0xafd9a63e,0xa63e2fd9,0x263eafd9,0xafd9a63e,0x2ea72c72,0x2c72aea7,0xac722ea7,0x2ea72c72,0xac72aea7,0xaea72c72,0x2ea7ac72,0xac72aea7,0x263e2fd9,0x2fd9a63e,0xafd9263e,0x263e2fd9,
0x2d13ae2f,0xae2fad13,0xa246aff6,0xaff62246,0xaf0eab8b,0xab8b2f0e,0xafa828a5,0x28a52fa8,0xa8a52fa8,0x2fa828a5,0x2b8b2f0e,0x2f0eab8b,0x2ff62246,0x2246aff6,0x2e2fad13,0xad13ae2f,
0xab8b2f0e,0x2f0e2b8b,0x2fa8a8a5,0xa8a5afa8,0x2ff6a246,0xa246aff6,0xae2fad13,0xad132e2f,0xad13ae2f,0xae2f2d13,0xa2462ff6,0x2ff62246,0xa8a52fa8,0x2fa828a5,0x2f0eab8b,0xab8baf0e,
0x28a5afa8,0xafa8a8a5,0x2b8b2f0e,0x2f0eab8b,0xae2f2d13,0x2d132e2f,0x2246aff6,0xaff6a246,0x2ff6a246,0xa246aff6,0xad132e2f,0x2e2f2d13,0xaf0eab8b,0xab8b2f0e,0x2fa8a8a5,0xa8a5afa8,
0xa2462ff6,0x2ff62246,0xae2f2d13,0x2d132e2f,0x28a5afa8,0xafa8a8a5,0x2f0eab8b,0xab8baf0e,0xab8b2f0e,0x2f0e2b8b,0xafa828a5,0x28a52fa8,0x2d13ae2f,0xae2fad13,0x2ff6a246,0xa246aff6,
0x30000000,0xb000,0x30000000,0xb000,0xb0000000,0x3000,0xb0000000,0x3000,0x30000000,0xb000,0x30000000,0xb000,0xb0000000,0x3000,0xb0000000,0x3000,
0xafd9263e,0x263e2fd9,0x263e2fd9,0x2fd9a63e,0x2ea7ac72,0xac72aea7,0xac72aea7,0xaea72c72,0xac722ea7,0x2ea72c72,0x2ea72c72,0x2c72aea7,0x263eafd9,0xafd9a63e,0xafd9a63e,0xa63e2fd9,
0x2f64aa1f,0xaa1faf64,0xaf642a1f,0x2a1f2f64,0xaa1f2f64,0x2f642a1f,0x2a1faf64,0xaf64aa1f,0xaa1faf64,0xaf642a1f,0x2a1f2f64,0x2f64aa1f,0x2f642a1f,0x2a1faf64,0xaf64aa1f,0xaa1f2f64,
0xaea72c72,0x2c722ea7,0xac72aea7,0xaea72c72,0xa63eafd9,0xafd9263e,0x2fd9a63e,0xa63eafd9,0x2fd9263e,0x263eafd9,0xa63e2fd9,0x2fd9263e,0xac722ea7,0x2ea72c72,0xaea7ac72,0xac722ea7,
0xa246aff6,0xaff62246,0xae2fad13,0xad132e2f,0x28a52fa8,0x2fa8a8a5,0x2f0e2b8b,0x2b8baf0e,0xab8baf0e,0xaf0e2b8b,0xafa8a8a5,0xa8a52fa8,0x2d132e2f,0x2e2fad13,0x2ff62246,0x2246aff6,
0x28a52fa8,0x2fa8a8a5,0x2b8baf0e,0xaf0eab8b,0xae2fad13,0xad132e2f,0x22462ff6,0x2ff6a246,0x2ff62246,0x2246aff6,0xad13ae2f,0xae2f2d13,0xaf0e2b8b,0x2b8b2f0e,0x2fa828a5,0x28a5afa8,
0xab8baf0e,0xaf0e2b8b,0x2fa828a5,0x28a5afa8,0x2ff62246,0x2246aff6,0xae2f2d13,0x2d132e2f,0xad132e2f,0x2e2f2d13,0xa246aff6,0xaff62246,0xa8a5afa8,0xafa828a5,0x2f0e2b8b,0x2b8baf0e,
0x2d132e2f,0x2e2fad13,0xa2462ff6,0x2ff62246,0xaf0e2b8b,0x2b8b2f0e,0xafa8a8a5,0xa8a52fa8,0xa8a5afa8,0xafa828a5,0x2b8baf0e,0xaf0eab8b,0x2ff6a246,0xa246aff6,0x2e2f2d13,0x2d13ae2f,
0x2da8ada8,0xada8ada8,0x2da8ada8,0xada8ada8,0x2da82da8,0x2da8ada8,0x2da82da8,0x2da8ada8,0xada82da8,0x2da82da8,0xada82da8,0x2da82da8,0xada8ada8,0xada82da8,0xada8ada8,0xada82da8,
0xac722ea7,0x2ea72c72,0x2ea72c72,0x2c72aea7,0xafd9a63e,0xa63e2fd9,0xa63e2fd9,0x2fd9263e,0xa63eafd9,0xafd9263e,0xafd9263e,0x263e2fd9,0x2ea7ac72,0xac72aea7,0xac72aea7,0xaea72c72,
0x2a1faf64,0xaf64aa1f,0xaa1f2f64,0x2f642a1f,0x2f64aa1f,0xaa1faf64,0xaf642a1f,0x2a1f2f64,0x2f642a1f,0x2a1faf64,0xaf64aa1f,0xaa1f2f64,0x2a1f2f64,0x2f64aa1f,0xaa1faf64,0xaf642a1f,
0xa63e2fd9,0x2fd9263e,0xafd9a63e,0xa63e2fd9,0xac722ea7,0x2ea72c72,0xaea7ac72,0xac722ea7,0xaea72c72,0x2c722ea7,0xac72aea7,0xaea72c72,0xafd9263e,0x263e2fd9,0xa63eafd9,0xafd9263e,
0xae2fad13,0xad132e2f,0xaff62246,0x22462ff6,0x2b8baf0e,0xaf0eab8b,0xa8a5afa8,0xafa828a5,0x2fa828a5,0x28a5afa8,0x2f0eab8b,0xab8baf0e,0xa2462ff6,0x2ff62246,0x2d132e2f,0x2e2fad13,
0x2f0e2b8b,0x2b8baf0e,0xa8a5afa8,0xafa828a5,0x22462ff6,0x2ff6a246,0x2d13ae2f,0xae2fad13,0xae2f2d13,0x2d132e2f,0x2ff62246,0x2246aff6,0xafa8a8a5,0xa8a52fa8,0x2b8b2f0e,0x2f0eab8b,
0xafa8a8a5,0xa8a52fa8,0x2f0eab8b,0xab8baf0e,0xad13ae2f,0xae2f2d13,0x2ff62246,0x2246aff6,0xa246aff6,0xaff62246,0x2e2f2d13,0x2d13ae2f,0x2b8baf0e,0xaf0eab8b,0x28a52fa8,0x2fa8a8a5,
0x2ff62246,0x2246aff6,0x2d132e2f,0x2e2fad13,0x2fa828a5,0x28a5afa8,0x2b8b2f0e,0x2f0eab8b,0x2f0e2b8b,0x2b8baf0e,0x28a52fa8,0x2fa8a8a5,0x2e2f2d13,0x2d13ae2f,0x22462ff6,0x2ff6a246,
0x3000,0x30008000,0x3000,0x30008000,0x3000,0x30008000,0x3000,0x30008000,0x3000,0x30008000,0x3000,0x30008000,0x3000,0x30008000,0x3000,0x30008000,
0x263e2fd9,0x2fd9a63e,0x2fd9a63e,0xa63eafd9,0x2c722ea7,0x2ea7ac72,0x2ea7ac72,0xac72aea7,0x2ea72c72,0x2c72aea7,0x2c72aea7,0xaea7ac72,0x2fd9263e,0x263eafd9,0x263eafd9,0xafd9a63e,
0x2a1f2f64,0x2f64aa1f,0xaa1faf64,0xaf642a1f,0x2f642a1f,0x2a1faf64,0xaf64aa1f,0xaa1f2f64,0x2f64aa1f,0xaa1faf64,0xaf642a1f,0x2a1f2f64,0x2a1faf64,0xaf64aa1f,0xaa1f2f64,0x2f642a1f,
0x2c722ea7,0x2ea7ac72,0xaea72c72,0x2c722ea7,0x2fd9a63e,0xa63eafd9,0x263e2fd9,0x2fd9a63e,0x263eafd9,0xafd9a63e,0x2fd9263e,0x263eafd9,0xaea7ac72,0xac722ea7,0x2c72aea7,0xaea7ac72,
0xa246aff6,0xaff62246,0xae2fad13,0xad132e2f,0xa8a5afa8,0xafa828a5,0xaf0eab8b,0xab8b2f0e,0xab8baf0e,0xaf0e2b8b,0xafa8a8a5,0xa8a52fa8,0xad13ae2f,0xae2f2d13,0xaff6a246,0xa2462ff6,
0xa8a5afa8,0xafa828a5,0xab8b2f0e,0x2f0e2b8b,0xae2fad13,0xad132e2f,0x22462ff6,0x2ff6a246,0xaff6a246,0xa2462ff6,0x2d132e2f,0x2e2fad13,0xaf0e2b8b,0x2b8b2f0e,0x2fa828a5,0x28a5afa8,
0xab8baf0e,0xaf0e2b8b,0x2fa828a5,0x28a5afa8,0xaff6a246,0xa2462ff6,0x2e2fad13,0xad13ae2f,0xad132e2f,0x2e2f2d13,0xa246aff6,0xaff62246,0x28a52fa8,0x2fa8a8a5,0xaf0eab8b,0xab8b2f0e,
0xad13ae2f,0xae2f2d13,0x2246aff6,0xaff6a246,0xaf0e2b8b,0x2b8b2f0e,0xafa8a8a5,0xa8a52fa8,0x28a52fa8,0x2fa8a8a5,0xab8b2f0e,0x2f0e2b8b,0x2ff6a246,0xa246aff6,0x2e2f2d13,0x2d13ae2f,
0x2da82da8,0x2da8ada8,0x2da82da8,0x2da8ada8,0x2da8ada8,0xada8ada8,0x2da8ada8,0xada8ada8,0xada8ada8,0xada82da8,0xada8ada8,0xada82da8,0xada82da8,0x2da82da8,0xada82da8,0x2da82da8,
0x2ea72c72,0x2c72aea7,0x2c72aea7,0xaea7ac72,0x263eafd9,0xafd9a63e,0xafd9a63e,0xa63e2fd9,0xafd9263e,0x263e2fd9,0x263e2fd9,0x2fd9a63e,0x2c722ea7,0x2ea7ac72,0x2ea7ac72,0xac72aea7,
0x2f642a1f,0x2a1faf64,0xaf64aa1f,0xaa1f2f64,0xaa1faf64,0xaf642a1f,0x2a1f2f64,0x2f64aa1f,0xaa1f2f64,0x2f642a1f,0x2a1faf64,0xaf64aa1f,0x2f64aa1f,0xaa1faf64,0xaf642a1f,0x2a1f2f64,
0x2fd9263e,0x263eafd9,0xa63e2fd9,0x2fd9263e,0xaea7ac72,0xac722ea7,0x2c72aea7,0xaea7ac72,0x2c722ea7,0x2ea7ac72,0xaea72c72,0x2c722ea7,0xa63eafd9,0xafd9263e,0x2fd9a63e,0xa63eafd9,
0xae2fad13,0xad132e2f,0xaff62246,0x22462ff6,0xab8b2f0e,0x2f0e2b8b,0x28a52fa8,0x2fa8a8a5,0x2fa828a5,0x28a5afa8,0x2f0eab8b,0xab8baf0e,0x2246aff6,0xaff6a246,0xad13ae2f,0xae2f2d13,
0xaf0eab8b,0xab8b2f0e,0x28a52fa8,0x2fa8a8a5,0x22462ff6,0x2ff6a246,0x2d13ae2f,0xae2fad13,0x2e2fad13,0xad13ae2f,0xaff6a246,0xa2462ff6,0xafa8a8a5,0xa8a52fa8,0x2b8b2f0e,0x2f0eab8b,
0xafa8a8a5,0xa8a52fa8,0x2f0eab8b,0xab8baf0e,0x2d132e2f,0x2e2fad13,0xaff6a246,0xa2462ff6,0xa246aff6,0xaff62246,0x2e2f2d13,0x2d13ae2f,0xab8b2f0e,0x2f0e2b8b,0xa8a5afa8,0xafa828a5,
0xaff6a246,0xa2462ff6,0xad13ae2f,0xae2f2d13,0x2fa828a5,0x28a5afa8,0x2b8b2f0e,0x2f0eab8b,0xaf0eab8b,0xab8b2f0e,0xa8a5afa8,0xafa828a5,0x2e2f2d13,0x2d13ae2f,0x22462ff6,0x2ff6a246,
0x30000000,0xb000,0x30000000,0xb000,0xb0000000,0x3000,0xb0000000,0x3000,0x30000000,0xb000,0x30000000,0xb000,0xb0000000,0x3000,0xb0000000,0x3000,
0x2fd9a63e,0xa63eafd9,0xa63eafd9,0xafd9263e,0xaea72c72,0x2c722ea7,0x2c722ea7,0x2ea7ac72,0x2c72aea7,0xaea7ac72,0xaea7ac72,0xac722ea7,0xa63e2fd9,0x2fd9263e,0x2fd9263e,0x263eafd9,
0x2f64aa1f,0xaa1faf64,0xaf642a1f,0x2a1f2f64,0xaa1f2f64,0x2f642a1f,0x2a1faf64,0xaf64aa1f,0xaa1faf64,0xaf642a1f,0x2a1f2f64,0x2f64aa1f,0x2f642a1f,0x2a1faf64,0xaf64aa1f,0xaa1f2f64,
0x2ea7ac72,0xac72aea7,0x2c722ea7,0x2ea7ac72,0x263e2fd9,0x2fd9a63e,0xafd9263e,0x263e2fd9,0xafd9a63e,0xa63e2fd9,0x263eafd9,0xafd9a63e,0x2c72aea7,0xaea7ac72,0x2ea72c72,0x2c72aea7,
0xaff62246,0x22462ff6,0xad132e2f,0x2e2f2d13,0x2fa8a8a5,0xa8a5afa8,0x2b8baf0e,0xaf0eab8b,0xaf0e2b8b,0x2b8b2f0e,0xa8a52fa8,0x2fa828a5,0x2e2fad13,0xad13ae2f,0x2246aff6,0xaff6a246,
0xafa828a5,0x28a52fa8,0x2f0e2b8b,0x2b8baf0e,0x2d13ae2f,0xae2fad13,0xaff62246,0x22462ff6,0xa2462ff6,0x2ff62246,0x2e2fad13,0xad13ae2f,0xab8baf0e,0xaf0e2b8b,0xa8a52fa8,0x2fa828a5,
0xaf0e2b8b,0x2b8b2f0e,0x28a5afa8,0xafa8a8a5,0x2246aff6,0xaff6a246,0x2d132e2f,0x2e2fad13,0x2e2f2d13,0x2d13ae2f,0xaff62246,0x22462ff6,0xafa828a5,0x28a52fa8,0x2b8baf0e,0xaf0eab8b,
0xae2f2d13,0x2d132e2f,0xaff6a246,0xa2462ff6,0xab8baf0e,0xaf0e2b8b,0x28a5afa8,0xafa8a8a5,0x2fa8a8a5,0xa8a5afa8,0x2f0e2b8b,0x2b8baf0e,0x22462ff6,0x2ff6a246,0xad132e2f,0x2e2f2d13,
0x2da8ada8,0xada8ada8,0x2da8ada8,0xada8ada8,0x2da82da8,0x2da8ada8,0x2da82da8,0x2da8ada8,0xada82da8,0x2da82da8,0xada82da8,0x2da82da8,0xada8ada8,0xada82da8,0xada8ada8,0xada82da8,
0x2c72aea7,0xaea7ac72,0xaea7ac72,0xac722ea7,0x2fd9263e,0x263eafd9,0x263eafd9,0xafd9a63e,0x263e2fd9,0x2fd9a63e,0x2fd9a63e,0xa63eafd9,0xaea72c72,0x2c722ea7,0x2c722ea7,0x2ea7ac72,
0x2a1faf64,0xaf64aa1f,0xaa1f2f64,0x2f642a1f,0x2f64aa1f,0xaa1faf64,0xaf642a1f,0x2a1f2f64,0x2f642a1f,0x2a1faf64,0xaf64aa1f,0xaa1f2f64,0x2a1f2f64,0x2f64aa1f,0xaa1faf64,0xaf642a1f,
0x263eafd9,0xafd9a63e,0x2fd9263e,0x263eafd9,0x2c72aea7,0xaea7ac72,0x2ea72c72,0x2c72aea7,0x2ea7ac72,0xac72aea7,0x2c722ea7,0x2ea7ac72,0x2fd9a63e,0xa63eafd9,0x263e2fd9,0x2fd9a63e,
0xad132e2f,0x2e2f2d13,0x22462ff6,0x2ff6a246,0xaf0eab8b,0xab8b2f0e,0xafa828a5,0x28a52fa8,0x28a5afa8,0xafa8a8a5,0xab8baf0e,0xaf0e2b8b,0x2ff62246,0x2246aff6,0x2e2fad13,0xad13ae2f,
0xab8b2f0e,0x2f0e2b8b,0x2fa8a8a5,0xa8a5afa8,0xaff62246,0x22462ff6,0x2e2f2d13,0x2d13ae2f,0xad13ae2f,0xae2f2d13,0xa2462ff6,0x2ff62246,0x28a5afa8,0xafa8a8a5,0xaf0e2b8b,0x2b8b2f0e,
0xa8a52fa8,0x2fa828a5,0xab8baf0e,0xaf0e2b8b,0xae2f2d13,0x2d132e2f,0x2246aff6,0xaff6a246,0xaff62246,0x22462ff6,0x2d13ae2f,0xae2fad13,0xaf0eab8b,0xab8b2f0e,0x2fa8a8a5,0xa8a5afa8,
0xa2462ff6,0x2ff62246,0xae2f2d13,0x2d132e2f,0xa8a52fa8,0x2fa828a5,0xaf0e2b8b,0x2b8b2f0e,0xab8b2f0e,0x2f0e2b8b,0xafa828a5,0x28a52fa8,0xad132e2f,0x2e2f2d13,0xaff62246,0x22462ff6,
0x3000,0x30008000,0x3000,0x30008000,0x3000,0x30008000,0x3000,0x30008000,0x3000,0x30008000,0x3000,0x30008000,0x3000,0x30008000,0x3000,0x30008000,
0xa63eafd9,0xafd9263e,0xafd9263e,0x263e2fd9,0xac72aea7,0xaea72c72,0xaea72c72,0x2c722ea7,0xaea7ac72,0xac722ea7,0xac722ea7,0x2ea72c72,0xafd9a63e,0xa63e2fd9,0xa63e2fd9,0x2fd9263e,
0x2a1f2f64,0x2f64aa1f,0xaa1faf64,0xaf642a1f,0x2f642a1f,0x2a1faf64,0xaf64aa1f,0xaa1f2f64,0x2f64aa1f,0xaa1faf64,0xaf642a1f,0x2a1f2f64,0x2a1faf64,0xaf64aa1f,0xaa1f2f64,0x2f642a1f,
0xac72aea7,0xaea72c72,0x2ea7ac72,0xac72aea7,0xafd9263e,0x263e2fd9,0xa63eafd9,0xafd9263e,0xa63e2fd9,0x2fd9263e,0xafd9a63e,0xa63e2fd9,0x2ea72c72,0x2c72aea7,0xac722ea7,0x2ea72c72,
0xaff62246,0x22462ff6,0xad132e2f,0x2e2f2d13,0xafa828a5,0x28a52fa8,0xab8b2f0e,0x2f0e2b8b,0xaf0e2b8b,0x2b8b2f0e,0xa8a52fa8,0x2fa828a5,0xae2f2d13,0x2d132e2f,0xa2462ff6,0x2ff62246,
0x2fa8a8a5,0xa8a5afa8,0xaf0eab8b,0xab8b2f0e,0x2d13ae2f,0xae2fad13,0xaff62246,0x22462ff6,0x2246aff6,0xaff6a246,0xae2f2d13,0x2d132e2f,0xab8baf0e,0xaf0e2b8b,0xa8a52fa8,0x2fa828a5,
0xaf0e2b8b,0x2b8b2f0e,0x28a5afa8,0xafa8a8a5,0xa2462ff6,0x2ff62246,0xad13ae2f,0xae2f2d13,0x2e2f2d13,0x2d13ae2f,0xaff62246,0x22462ff6,0x2fa8a8a5,0xa8a5afa8,0xab8b2f0e,0x2f0e2b8b,
0x2e2fad13,0xad13ae2f,0x2ff62246,0x2246aff6,0xab8baf0e,0xaf0e2b8b,0x28a5afa8,0xafa8a8a5,0xafa828a5,0x28a52fa8,0xaf0eab8b,0xab8b2f0e,0x22462ff6,0x2ff6a246,0xad132e2f,0x2e2f2d13,
0x2da82da8,0x2da8ada8,0x2da82da8,0x2da8ada8,0x2da8ada8,0xada8ada8,0x2da8ada8,0xada8ada8,0xada8ada8,0xada82da8,0xada8ada8,0xada82da8,0xada82da8,0x2da82da8,0xada82da8,0x2da82da8,
0xaea7ac72,0xac722ea7,0xac722ea7,0x2ea72c72,0xa63e2fd9,0x2fd9263e,0x2fd9263e,0x263eafd9,0x2fd9a63e,0xa63eafd9,0xa63eafd9,0xafd9263e,0xac72aea7,0xaea72c72,0xaea72c72,0x2c722ea7,
0x2f642a1f,0x2a1faf64,0xaf64aa1f,0xaa1f2f64,0xaa1faf64,0xaf642a1f,0x2a1f2f64,0x2f64aa1f,0xaa1f2f64,0x2f642a1f,0x2a1faf64,0xaf64aa1f,0x2f64aa1f,0xaa1faf64,0xaf642a1f,0x2a1f2f64,
0xafd9a63e,0xa63e2fd9,0x263eafd9,0xafd9a63e,0x2ea72c72,0x2c72aea7,0xac722ea7,0x2ea72c72,0xac72aea7,0xaea72c72,0x2ea7ac72,0xac72aea7,0x263e2fd9,0x2fd9a63e,0xafd9263e,0x263e2fd9,
0xad132e2f,0x2e2f2d13,0x22462ff6,0x2ff6a246,0x2f0e2b8b,0x2b8baf0e,0x2fa8a8a5,0xa8a5afa8,0x28a5afa8,0xafa8a8a5,0xab8baf0e,0xaf0e2b8b,0xaff6a246,0xa2462ff6,0xae2f2d13,0x2d132e2f,
0x2b8baf0e,0xaf0eab8b,0xafa828a5,0x28a52fa8,0xaff62246,0x22462ff6,0x2e2f2d13,0x2d13ae2f,0x2d132e2f,0x2e2fad13,0x2246aff6,0xaff6a246,0x28a5afa8,0xafa8a8a5,0xaf0e2b8b,0x2b8b2f0e,
0xa8a52fa8,0x2fa828a5,0xab8baf0e,0xaf0e2b8b,0x2e2fad13,0xad13ae2f,0xa2462ff6,0x2ff62246,0xaff62246,0x22462ff6,0x2d13ae2f,0xae2fad13,0x2f0e2b8b,0x2b8baf0e,0xafa828a5,0x28a52fa8,
0x2246aff6,0xaff6a246,0x2e2fad13,0xad13ae2f,0xa8a52fa8,0x2fa828a5,0xaf0e2b8b,0x2b8b2f0e,0x2b8baf0e,0xaf0eab8b,0x2fa8a8a5,0xa8a5afa8,0xad132e2f,0x2e2f2d13,0xaff62246,0x22462ff6,
0x30000000,0xb000,0x30000000,0xb000,0xb0000000,0x3000,0xb0000000,0x3000,0x30000000,0xb000,0x30000000,0xb000,0xb0000000,0x3000,0xb0000000,0x3000,
0xafd9263e,0x263e2fd9,0x263e2fd9,0x2fd9a63e,0x2ea7ac72,0xac72aea7,0xac72aea7,0xaea72c72,0xac722ea7,0x2ea72c72,0x2ea72c72,0x2c72aea7,0x263eafd9,0xafd9a63e,0xafd9a63e,0xa63e2fd9,
0x2f64aa1f,0xaa1faf64,0xaf642a1f,0x2a1f2f64,0xaa1f2f64,0x2f642a1f,0x2a1faf64,0xaf64aa1f,0xaa1faf64,0xaf642a1f,0x2a1f2f64,0x2f64aa1f,0x2f642a1f,0x2a1faf64,0xaf64aa1f,0xaa1f2f64,
0xaea72c72,0x2c722ea7,0xac72aea7,0xaea72c72,0xa63eafd9,0xafd9263e,0x2fd9a63e,0xa63eafd9,0x2fd9263e,0x263eafd9,0xa63e2fd9,0x2fd9263e,0xac722ea7,0x2ea72c72,0xaea7ac72,0xac722ea7,
0x22462ff6,0x2ff6a246,0x2e2f2d13,0x2d13ae2f,0xa8a5afa8,0xafa828a5,0xaf0eab8b,0xab8b2f0e,0x2b8b2f0e,0x2f0eab8b,0x2fa828a5,0x28a5afa8,0xad13ae2f,0xae2f2d13,0xaff6a246,0xa2462ff6,
0xa8a5afa8,0xafa828a5,0xab8b2f0e,0x2f0e2b8b,0x2e2f2d13,0x2d13ae2f,0xa246aff6,0xaff62246,0xaff6a246,0xa2462ff6,0x2d132e2f,0x2e2fad13,0x2f0eab8b,0xab8baf0e,0xafa8a8a5,0xa8a52fa8,
0x2b8b2f0e,0x2f0eab8b,0xafa8a8a5,0xa8a52fa8,0xaff6a246,0xa2462ff6,0x2e2fad13,0xad13ae2f,0x2d13ae2f,0xae2fad13,0x22462ff6,0x2ff6a246,0x28a52fa8,0x2fa8a8a5,0xaf0eab8b,0xab8b2f0e,
0xad13ae2f,0xae2f2d13,0x2246aff6,0xaff6a246,0x2f0eab8b,0xab8baf0e,0x2fa828a5,0x28a5afa8,0x28a52fa8,0x2fa8a8a5,0xab8b2f0e,0x2f0e2b8b,0xaff62246,0x22462ff6,0xae2fad13,0xad132e2f,
0x2da8ada8,0xada8ada8,0x2da8ada8,0xada8ada8,0x2da82da8,0x2da8ada8,0x2da82da8,0x2da8ada8,0xada82da8,0x2da82da8,0xada82da8,0x2da82da8,0xada8ada8,0xada82da8,0xada8ada8,0xada82da8,
0xac722ea7,0x2ea72c72,0x2ea72c72,0x2c72aea7,0xafd9a63e,0xa63e2fd9,0xa63e2fd9,0x2fd9263e,0xa63eafd9,0xafd9263e,0xafd9263e,0x263e2fd9,0x2ea7ac72,0xac72aea7,0xac72aea7,0xaea72c72,
0x2a1faf64,0xaf64aa1f,0xaa1f2f64,0x2f642a1f,0x2f64aa1f,0xaa1faf64,0xaf642a1f,0x2a1f2f64,0x2f642a1f,0x2a1faf64,0xaf64aa1f,0xaa1f2f64,0x2a1f2f64,0x2f64aa1f,0xaa1faf64,0xaf642a1f,
0xa63e2fd9,0x2fd9263e,0xafd9a63e,0xa63e2fd9,0xac722ea7,0x2ea72c72,0xaea7ac72,0xac722ea7,0xaea72c72,0x2c722ea7,0xac72aea7,0xaea72c72,0xafd9263e,0x263e2fd9,0xa63eafd9,0xafd9263e,
0x2e2f2d13,0x2d13ae2f,0x2ff6a246,0xa246aff6,0xab8b2f0e,0x2f0e2b8b,0x28a52fa8,0x2fa8a8a5,0xafa8a8a5,0xa8a52fa8,0xaf0e2b8b,0x2b8b2f0e,0x2246aff6,0xaff6a246,0xad13ae2f,0xae2f2d13,
0xaf0eab8b,0xab8b2f0e,0x28a52fa8,0x2fa8a8a5,0xa246aff6,0xaff62246,0xad132e2f,0x2e2f2d13,0x2e2fad13,0xad13ae2f,0xaff6a246,0xa2462ff6,0x2fa828a5,0x28a5afa8,0xab8baf0e,0xaf0e2b8b,
0x2fa828a5,0x28a5afa8,0xaf0e2b8b,0x2b8b2f0e,0x2d132e2f,0x2e2fad13,0xaff6a246,0xa2462ff6,0x22462ff6,0x2ff6a246,0xae2fad13,0xad132e2f,0xab8b2f0e,0x2f0e2b8b,0xa8a5afa8,0xafa828a5,
0xaff6a246,0xa2462ff6,0xad13ae2f,0xae2f2d13,0xafa8a8a5,0xa8a52fa8,0xab8baf0e,0xaf0e2b8b,0xaf0eab8b,0xab8b2f0e,0xa8a5afa8,0xafa828a5,0xae2fad13,0xad132e2f,0xa246aff6,0xaff62246,
0x3f800000,0,0x3f800000,0,0x3f800000,0,0x3f800000,0,0x3f800000,0,0x3f800000,0,0x3f800000,0,0x3f800000,0,
0x3f800000,0,0x3f7ffec4,0x3bc90f88,0x3f7ffb11,0x3c490e90,0x3f7ff4e6,0x3c96c9b6,0x3f7fec43,0x3cc90ab0,0x3f7fe129,0x3cfb49ba,0x3f7fd397,0x3d16c32c,0x3f7fc38f,0x3d2fe007,
0x3f800000,0,0x3f7ffb11,0x3c490e90,0x3f7fec43,0x3cc90ab0,0x3f7fd397,0x3d16c32c,0x3f7fb10f,0x3d48fb30,0x3f7f84ab,0x3d7b2b74,0x3f7f4e6d,0x3d96a905,0x3f7f0e58,0x3dafb680,
0x3f800000,0,0x3f7ff4e6,0x3c96c9b6,0x3f7fd397,0x3d16c32c,0x3f7f9c18,0x3d621469,0x3f7f4e6d,0x3d96a905,0x3f7eea9d,0x3dbc3ac3,0x3f7e70b0,0x3de1bc2e,0x3f7de0b1,0x3e039502,
0x3f800000,0,0x3f7fffb1,0x3b490fc6,0x3f7ffec4,0x3bc90f88,0x3f7ffd39,0x3c16cb58,0x3f7ffb11,0x3c490e90,0x3f7ff84a,0x3c7b514b,0x3f7ff4e6,0x3c96c9b6,0x3f7ff0e3,0x3cafea69,
0x3f800000,0,0x3f7ffd39,0x3c16cb58,0x3f7ff4e6,0x3c96c9b6,0x3f7fe705,0x3ce22a7a,0x3f7fd397,0x3d16c32c,0x3f7fba9e,0x3d3c6dd5,0x3f7f9c18,0x3d621469,0x3f7f7808,0x3d83db0a,
0x3f800000,0,0x3f7ff84a,0x3c7b514b,0x3f7fe129,0x3cfb49ba,0x3f7fba9e,0x3d3c6dd5,0x3f7f84ab,0x3d7b2b74,0x3f7f3f54,0x3d9cecf9,0x3f7eea9d,0x3dbc3ac3,0x3f7e868b,0x3ddb7d37,
0x3f800000,0,0x3f7ff0e3,0x3cafea69,0x3f7fc38f,0x3d2fe007,0x3f7f7808,0x3d83db0a,0x3f7f0e58,0x3dafb680,0x3f7e868b,0x3ddb7d37,0x3f7de0b1,0x3e039502,0x3f7d1cdd,0x3e195be0,
0x3f800000,0,0x3f7fec43,0x3cc90ab0,0x3f7fb10f,0x3d48fb30,0x3f7f4e6d,0x3d96a905,0x3f7ec46d,0x3dc8bd36,0x3f7e1324,0x3dfab273,0x3f7d3aac,0x3e164083,0x3f7c3b28,0x3e2f10a2,
0x3f800000,0,0x3f7fe129,0x3cfb49ba,0x3f7f84ab,0x3d7b2b74,0x3f7eea9d,0x3dbc3ac3,0x3f7e1324,0x3dfab273,0x3f7cfe73,0x3e1c76de,0x3f7baccd,0x3e3b6ecf,0x3f7a1e84,0x3e5a3997,
0x3f800000,0,0x3f7fd397,0x3d16c32c,0x3f7f4e6d,0x3d96a905,0x3f7e70b0,0x3de1bc2e,0x3f7d3aac,0x3e164083,0x3f7baccd,0x3e3b6ecf,0x3f79c79d,0x3e605c13,0x3f778bc5,0x3e827dc0,
0x3f800000,0,0x3f7fc38f,0x3d2fe007,0x3f7f0e58,0x3dafb680,0x3f7de0b1,0x3e039502,0x3f7c3b28,0x3e2f10a2,0x3f7a1e84,0x3e5a3997,0x3f778bc5,0x3e827dc0,0x3f748422,0x3e97a117,
0x3f800000,0,0x3f7fe705,0x3ce22a7a,0x3f7f9c18,0x3d621469,0x3f7f1f49,0x3da973ba,0x3f7e70b0,0x3de1bc2e,0x3f7d906e,0x3e0cec4a,0x3f7c7eb0,0x3e28defc,0x3f7b3bab,0x3e44b0b9,
0x3f800000,0,0x3f7fdaaf,0x3d0a342f,0x3f7f6ac7,0x3d8a200a,0x3f7eb069,0x3dcefdb7,0x3f7dabcc,0x3e09cf86,0x3f7c5d3a,0x3e2bf804,0x3f7ac516,0x3e4dee60,0x3f78e3d6,0x3e6fa8b2,
0x3f800000,0,0x3f7fcbe2,0x3d2351cb,0x3f7f2f9d,0x3da3308c,0x3f7e2b72,0x3df475c0,0x3f7cbfc9,0x3e22abb6,0x3f7aed37,0x3e4ada4f,0x3f78b47b,0x3e72b651,0x3f76167a,0x3e8d17c0,
0x3f800000,0,0x3f7fba9e,0x3d3c6dd5,0x3f7eea9d,0x3dbc3ac3,0x3f7d906e,0x3e0cec4a,0x3f7baccd,0x3e3b6ecf,0x3f7940c0,0x3e698bba,0x3f764d97,0x3e8b9507,0x3f72d4eb,0x3ea21887,
0x3f800000,0,0x3f7fb10f,0x3d48fb30,0x3f7ec46d,0x3dc8bd36,0x3f7d3aac,0x3e164083,0x3f7b14be,0x3e47c5c2,0x3f7853f8,0x3e78cfcc,0x3f74fa0b,0x3e94a031,0x3f710908,0x3eac7cd4,
0x3f800000,0,0x3f7f9c18,0x3d621469,0x3f7e70b0,0x3de1bc2e,0x3f7c7eb0,0x3e28defc,0x3f79c79d,0x3e605c13,0x3f764d97,0x3e8b9507,0x3f721352,0x3ea68f12,0x3f6d1c1d,0x3ec1071e,
0x3f800000,0,0x3f7f84ab,0x3d7b2b74,0x3f7e1324,0x3dfab273,0x3f7baccd,0x3e3b6ecf,0x3f7853f8,0x3e78cfcc,0x3f740bdd,0x3e9aa086,0x3f6ed89e,0x3eb8442a,0x3f68bf3c,0x3ed53641,
0x3f800000,0,0x3f7f6ac7,0x3d8a200a,0x3f7dabcc,0x3e09cf86,0x3f7ac516,0x3e4dee60,0x3f76ba07,0x3e888e93,0x3f718f57,0x3ea986c4,0x3f6b4b0c,0x3ec9b953,0x3f63f473,0x3ee900b7,
0x3f800000,0,0x3f7fa6e3,0x3d55880e,0x3f7e9bc9,0x3dd53db9,0x3f7cdf6c,0x3e1f917b,0x3f7a7302,0x3e541501,0x3f77583a,0x3e840270,0x3f73913f,0x3e9d9e78,0x3f6f20b0,0x3eb6ccc3,
0x3f800000,0,0x3f7f90b1,0x3d6ea038,0x3f7e4323,0x3dee3876,0x3f7c187a,0x3e3228d4,0x3f791298,0x3e6c9a7f,0x3f75341d,0x3e931f35,0x3f708066,0x3eaf713a,0x3f6afb8c,0x3ecb2aae,
0x3f800000,0,0x3f7f7808,0x3d83db0a,0x3f7de0b1,0x3e039502,0x3f7b3bab,0x3e44b0b9,0x3f778bc5,0x3e827dc0,0x3f72d4eb,0x3ea21887,0x3f6d1c1d,0x3ec1071e,0x3f666771,0x3edf28a9,
0x3f800000,0,0x3f7f5ce9,0x3d9064b4,0x3f7d7474,0x3e1008b7,0x3f7a4910,0x3e57278f,0x3f75dec6,0x3e8e9a22,0x3f703b37,0x3eb0eacb,0x3f696591,0x3ed25a09,0x3f61668a,0x3ef2bd43,
0x3f800000,0,0x3f7f4e6d,0x3d96a905,0x3f7d3aac,0x3e164083,0x3f79c79d,0x3e605c13,0x3f74fa0b,0x3e94a031,0x3f6ed89e,0x3eb8442a,0x3f676bd8,0x3edae880,0x3f5ebe05,0x3efc5d27,
0x3f800000,0,0x3f7f2f9d,0x3da3308c,0x3f7cbfc9,0x3e22abb6,0x3f78b47b,0x3e72b651,0x3f731447,0x3ea09ae5,0x3f6be858,0x3ec6d529,0x3f633c5a,0x3eebcbbb,0x3f591e6a,0x3f07a136,
0x3f800000,0,0x3f7f0e58,0x3dafb680,0x3f7c3b28,0x3e2f10a2,0x3f778bc5,0x3e827dc0,0x3f710908,0x3eac7cd4,0x3f68bf3c,0x3ed53641,0x3f5ebe05,0x3efc5d27,0x3f531849,0x3f10d3cd,
0x3f800000,0,0x3f7eea9d,0x3dbc3ac3,0x3f7baccd,0x3e3b6ecf,0x3f764d97,0x3e8b9507,0x3f6ed89e,0x3eb8442a,0x3f655e0b,0x3ee363fa,0x3f59f26a,0x3f064b82,0x3f4cae79,0x3f19c200,
0x3f800000,0,0x3f7f3f54,0x3d9cecf9,0x3f7cfe73,0x3e1c76de,0x3f7940c0,0x3e698bba,0x3f740bdd,0x3e9aa086,0x3f6d67a1,0x3ebf926f,0x3f655e0b,0x3ee363fa,0x3f5bfb34,0x3f02ef9f,
0x3f800000,0,0x3f7f1f49,0x3da973ba,0x3f7c7eb0,0x3e28defc,0x3f7822d1,0x3e7bdba4,0x3f721352,0x3ea68f12,0x3f6a5ad9,0x3ece0bea,0x3f6106f2,0x3ef41f07,0x3f5627fe,0x3f0c42c9,
0x3f800000,0,0x3f7efcc9,0x3db5f8da,0x3f7bf531,0x3e354098,0x3f76ef5b,0x3e870ada,0x3f6ff573,0x3eb263ef,0x3f671599,0x3edc53c1,0x3f5c61c7,0x3f0242b1,0x3f4fefa8,0x3f1553b7,
0x3f800000,0,0x3f7ed7d4,0x3dc27c39,0x3f7b61fc,0x3e419b37,0x3f75a67b,0x3e901c2c,0x3f6db293,0x3ebe1d4a,0x3f6398ac,0x3eea6681,0x3f577026,0x3f0a48ad,0x3f495521,0x3f1e1e22,
0x3f800000,0,0x3f7ec46d,0x3dc8bd36,0x3f7b14be,0x3e47c5c2,0x3f74fa0b,0x3e94a031,0x3f6c835e,0x3ec3ef15,0x3f61c598,0x3ef15aea,0x3f54db31,0x3f0e39da,0x3f45e403,0x3f226799,
0x3f800000,0,0x3f7e9bc9,0x3dd53db9,0x3f7a7302,0x3e541501,0x3f73913f,0x3e9d9e78,0x3f6a09a7,0x3ecf7bca,0x3f5df6be,0x3eff17b2,0x3f4f7a1f,0x3f15f6d9,0x3f3ebc1b,0x3f2ac082,
0x3f800000,0,0x3f7e70b0,0x3de1bc2e,0x3f79c79d,0x3e605c13,0x3f721352,0x3ea68f12,0x3f676bd8,0x3edae880,0x3f59f26a,0x3f064b82,0x3f49d112,0x3f1d7fd1,0x3f373a23,0x3f32c8c9,
0x3f800000,0,0x3f7e4323,0x3dee3876,0x3f791298,0x3e6c9a7f,0x3f708066,0x3eaf713a,0x3f64aa59,0x3ee63375,0x3f55b993,0x3f0cead0,0x3f43e200,0x3f24d225,0x3f2f61a5,0x3f3a7ca4,
0x3f800000,0,0x3f7eb069,0x3dcefdb7,0x3f7ac516,0x3e4dee60,0x3f74484b,0x3e9920fe,0x3f6b4b0c,0x3ec9b953,0x3f5fe4e9,0x3ef840c8,0x3f5233c6,0x3f121eb0,0x3f425b89,0x3f269de3,
0x3f800000,0,0x3f7e868b,0x3ddb7d37,0x3f7a1e84,0x3e5a3997,0x3f72d4eb,0x3ea21887,0x3f68bf3c,0x3ed53641,0x3f5bfb34,0x3f02ef9f,0x3f4cae79,0x3f19c200,0x3f3b0629,0x3f2ecef7,
0x3f800000,0,0x3f7e5a38,0x3de7fa9a,0x3f796e4e,0x3e667c66,0x3f714c7a,0x3eab0201,0x3f660f88,0x3ee0924f,0x3f57dc7f,0x3f099f4e,0x3f46e22a,0x3f212ff9,0x3f33587a,0x3f36ad7f,
0x3f800000,0,0x3f7e2b72,0x3df475c0,0x3f78b47b,0x3e72b651,0x3f6faf1b,0x3eb3dca5,0x3f633c5a,0x3eebcbbb,0x3f5389c7,0x3f102dd5,0x3f40d0da,0x3f286605,0x3f2b561b,0x3f3e35c5,
0x3f800000,0,0x3f7e1324,0x3dfab273,0x3f7853f8,0x3e78cfcc,0x3f6ed89e,0x3eb8442a,0x3f61c598,0x3ef15aea,0x3f514d3d,0x3f13682a,0x3f3daef9,0x3f2beb4a,0x3f273656,0x3f41d870,
0x3f800000,0,0x3f7de0b1,0x3e039502,0x3f778bc5,0x3e827dc0,0x3f6d1c1d,0x3ec1071e,0x3f5ebe05,0x3efc5d27,0x3f4cae79,0x3f19c200,0x3f373a23,0x3f32c8c9,0x3f1ebc12,0x3f48d8b3,
0x3f800000,0,0x3f7dabcc,0x3e09cf86,0x3f76ba07,0x3e888e93,0x3f6b4b0c,0x3ec9b953,0x3f5b941a,0x3f039c3d,0x3f47de65,0x3f1ff6cb,0x3f3085bb,0x3f396842,0x3f15f6d9,0x3f4f7a1f,
0x3f800000,0,0x3f7d7474,0x3e1008b7,0x3f75dec6,0x3e8e9a22,0x3f696591,0x3ed25a09,0x3f584853,0x3f08f59b,0x3f42de29,0x3f26050a,0x3f299415,0x3f3fc767,0x3f0cead0,0x3f55b993,
0x3f800000,0,0x3f7dfa38,0x3e007745,0x3f77f110,0x3e7ee6e1,0x3f6dfcf2,0x3ebca7af,0x3f604621,0x3ef6e0cb,0x3f4f0417,0x3f16999f,0x3f3a7ca4,0x3f2f61a5,0x3f2302d3,0x3f456439,
0x3f800000,0,0x3f7dc68c,0x3e06b26e,0x3f772417,0x3e8586ce,0x3f6c3624,0x3ec5625c,0x3f5d2d53,0x3f00e7e4,0x3f4a4c87,0x3f1ce11f,0x3f33e7bc,0x3f36206c,0x3f1a6293,0x3f4c3578,
0x3f800000,0,0x3f7d906e,0x3e0cec4a,0x3f764d97,0x3e8b9507,0x3f6a5ad9,0x3ece0bea,0x3f59f26a,0x3f064b82,0x3f456439,0x3f2302d3,0x3f2d1469,0x3f3ca003,0x3f11796b,0x3f52a649,
0x3f800000,0,0x3f7d57de,0x3e1324ca,0x3f756d97,0x3e919ddd,0x3f686b39,0x3ed6a399,0x3f5695e5,0x3f0b9a6b,0x3f404c5c,0x3f28fd41,0x3f26050a,0x3f42de29,0x3f084b92,0x3f58b3a1,
0x3f800000,0,0x3f7d3aac,0x3e164083,0x3f74fa0b,0x3e94a031,0x3f676bd8,0x3edae880,0x3f54db31,0x3f0e39da,0x3f3daef9,0x3f2beb4a,0x3f226799,0x3f45e403,0x3f039c3d,0x3f5b941a,
0x3f800000,0,0x3f7cfe73,0x3e1c76de,0x3f740bdd,0x3e9aa086,0x3f655e0b,0x3ee363fa,0x3f514d3d,0x3f13682a,0x3f385216,0x3f31a81d,0x3f1b02c6,0x3f4bbbf8,0x3ef41f07,0x3f6106f2,
0x3f800000,0,0x3f7cbfc9,0x3e22abb6,0x3f731447,0x3ea09ae5,0x3f633c5a,0x3eebcbbb,0x3f4d9f02,0x3f187fc0,0x3f32c8c9,0x3f373a23,0x3f13682a,0x3f514d3d,0x3ee0924f,0x3f660f88,
0x3f800000,0,0x3f7c7eb0,0x3e28defc,0x3f721352,0x3ea68f12,0x3f6106f2,0x3ef41f07,0x3f49d112,0x3f1d7fd1,0x3f2d1469,0x3f3ca003,0x3f0b9a6b,0x3f5695e5,0x3ecc9b8b,0x3f6aab7b,
0x3f800000,0,0x3f7d1cdd,0x3e195be0,0x3f748422,0x3e97a117,0x3f666771,0x3edf28a9,0x3f531849,0x3f10d3cd,0x3f3b0629,0x3f2ecef7,0x3f1ebc12,0x3f48d8b3,0x3efdbabb,0x3f5e5aa6,
0x3f800000,0,0x3f7cdf6c,0x3e1f917b,0x3f73913f,0x3e9d9e78,0x3f644fac,0x3ee79a5d,0x3f4f7a1f,0x3f15f6d9,0x3f3592e7,0x3f34768f,0x3f173c07,0x3f4e8d90,0x3eea6681,0x3f6398ac,
0x3f800000,0,0x3f7c9f8a,0x3e25c58c,0x3f7294f8,0x3ea395c5,0x3f62241a,0x3eeff7fb,0x3f4bbbf8,0x3f1b02c6,0x3f2ff3e6,0x3f39f2ac,0x3f0f8784,0x3f53fac3,0x3ed6a399,0x3f686b39,
0x3f800000,0,0x3f7c5d3a,0x3e2bf804,0x3f718f57,0x3ea986c4,0x3f5fe4e9,0x3ef840c8,0x3f47de65,0x3f1ff6cb,0x3f2a2a80,0x3f3f41fc,0x3f07a136,0x3f591e6a,0x3ec27b55,0x3f6cd007,
0x3f800000,0,0x3f7c3b28,0x3e2f10a2,0x3f710908,0x3eac7cd4,0x3f5ebe05,0x3efc5d27,0x3f45e403,0x3f226799,0x3f273656,0x3f41d870,0x3f039c3d,0x3f5b941a,0x3eb8442a,0x3f6ed89e,
0x3f800000,0,0x3f7bf531,0x3e354098,0x3f6ff573,0x3eb263ef,0x3f5c61c7,0x3f0242b1,0x3f41d870,0x3f273656,0x3f212ff9,0x3f46e22a,0x3ef6e0cb,0x3f604621,0x3ea395c5,0x3f7294f8,
0x3f800000,0,0x3f7baccd,0x3e3b6ecf,0x3f6ed89e,0x3eb8442a,0x3f59f26a,0x3f064b82,0x3f3daef9,0x3f2beb4a,0x3f1b02c6,0x3f4bbbf8,0x3ee63375,0x3f64aa59,0x3e8e9a22,0x3f75dec6,
0x3f800000,0,0x3f7b61fc,0x3e419b37,0x3f6db293,0x3ebe1d4a,0x3f577026,0x3f0a48ad,0x3f396842,0x3f3085bb,0x3f14b039,0x3f5064af,0x3ed53641,0x3f68bf3c,0x3e72b651,0x3f78b47b,
0x3f800000,0,0x3f7c187a,0x3e3228d4,0x3f708066,0x3eaf713a,0x3f5d924d,0x3f003a06,0x3f43e200,0x3f24d225,0x3f24381a,0x3f446337,0x3eff17b2,0x3f5df6be,0x3eadf73c,0x3f70c501,
0x3f800000,0,0x3f7bd14d,0x3e3857ec,0x3f6f6830,0x3eb554ec,0x3f5b2c79,0x3f044889,0x3f3fc767,0x3f299415,0x3f1e1e22,0x3f495521,0x3eee9479,0x3f628210,0x3e9920fe,0x3f74484b,
0x3f800000,0,0x3f7b87b2,0x3e3e853e,0x3f6e46be,0x3ebb31a0,0x3f58b3a1,0x3f084b92,0x3f3b8f3b,0x3f2e3bde,0x3f17de12,0x3f4e1689,0x3eddbe79,0x3f66becc,0x3e840270,0x3f77583a,
0x3f800000,0,0x3f7b3bab,0x3e44b0b9,0x3f6d1c1d,0x3ec1071e,0x3f5627fe,0x3f0c42c9,0x3f373a23,0x3f32c8c9,0x3f11796b,0x3f52a649,0x3ecc9b8b,0x3f6aab7b,0x3e5d4b1a,0x3f79f35e,
0x3f800000,0,0x3f800000,0,0x3f800000,0,0x3f800000,0,0x3f800000,0,0x3f800000,0,0x3f800000,0,0x3f800000,0,
0x3f7fb10f,0x3d48fb30,0x3f7f9c18,0x3d621469,0x3f7f84ab,0x3d7b2b74,0x3f7f6ac7,0x3d8a200a,0x3f7f4e6d,0x3d96a905,0x3f7f2f9d,0x3da3308c,0x3f7f0e58,0x3dafb680,0x3f7eea9d,0x3dbc3ac3,
0x3f7ec46d,0x3dc8bd36,0x3f7e70b0,0x3de1bc2e,0x3f7e1324,0x3dfab273,0x3f7dabcc,0x3e09cf86,0x3f7d3aac,0x3e164083,0x3f7cbfc9,0x3e22abb6,0x3f7c3b28,0x3e2f10a2,0x3f7baccd,0x3e3b6ecf,
0x3f7d3aac,0x3e164083,0x3f7c7eb0,0x3e28defc,0x3f7baccd,0x3e3b6ecf,0x3f7ac516,0x3e4dee60,0x3f79c79d,0x3e605c13,0x3f78b47b,0x3e72b651,0x3f778bc5,0x3e827dc0,0x3f764d97,0x3e8b9507,
0x3f7fec43,0x3cc90ab0,0x3f7fe705,0x3ce22a7a,0x3f7fe129,0x3cfb49ba,0x3f7fdaaf,0x3d0a342f,0x3f7fd397,0x3d16c32c,0x3f7fcbe2,0x3d2351cb,0x3f7fc38f,0x3d2fe007,0x3f7fba9e,0x3d3c6dd5,
0x3f7f4e6d,0x3d96a905,0x3f7f1f49,0x3da973ba,0x3f7eea9d,0x3dbc3ac3,0x3f7eb069,0x3dcefdb7,0x3f7e70b0,0x3de1bc2e,0x3f7e2b72,0x3df475c0,0x3f7de0b1,0x3e039502,0x3f7d906e,0x3e0cec4a,
0x3f7e1324,0x3dfab273,0x3f7d906e,0x3e0cec4a,0x3f7cfe73,0x3e1c76de,0x3f7c5d3a,0x3e2bf804,0x3f7baccd,0x3e3b6ecf,0x3f7aed37,0x3e4ada4f,0x3f7a1e84,0x3e5a3997,0x3f7940c0,0x3e698bba,
0x3f7c3b28,0x3e2f10a2,0x3f7b3bab,0x3e44b0b9,0x3f7a1e84,0x3e5a3997,0x3f78e3d6,0x3e6fa8b2,0x3f778bc5,0x3e827dc0,0x3f76167a,0x3e8d17c0,0x3f748422,0x3e97a117,0x3f72d4eb,0x3ea21887,
0x3f7b14be,0x3e47c5c2,0x3f79c79d,0x3e605c13,0x3f7853f8,0x3e78cfcc,0x3f76ba07,0x3e888e93,0x3f74fa0b,0x3e94a031,0x3f731447,0x3ea09ae5,0x3f710908,0x3eac7cd4,0x3f6ed89e,0x3eb8442a,
0x3f7853f8,0x3e78cfcc,0x3f764d97,0x3e8b9507,0x3f740bdd,0x3e9aa086,0x3f718f57,0x3ea986c4,0x3f6ed89e,0x3eb8442a,0x3f6be858,0x3ec6d529,0x3f68bf3c,0x3ed53641,0x3f655e0b,0x3ee363fa,
0x3f74fa0b,0x3e94a031,0x3f721352,0x3ea68f12,0x3f6ed89e,0x3eb8442a,0x3f6b4b0c,0x3ec9b953,0x3f676bd8,0x3edae880,0x3f633c5a,0x3eebcbbb,0x3f5ebe05,0x3efc5d27,0x3f59f26a,0x3f064b82,
0x3f710908,0x3eac7cd4,0x3f6d1c1d,0x3ec1071e,0x3f68bf3c,0x3ed53641,0x3f63f473,0x3ee900b7,0x3f5ebe05,0x3efc5d27,0x3f591e6a,0x3f07a136,0x3f531849,0x3f10d3cd,0x3f4cae79,0x3f19c200,
0x3f79c79d,0x3e605c13,0x3f7822d1,0x3e7bdba4,0x3f764d97,0x3e8b9507,0x3f74484b,0x3e9920fe,0x3f721352,0x3ea68f12,0x3f6faf1b,0x3eb3dca5,0x3f6d1c1d,0x3ec1071e,0x3f6a5ad9,0x3ece0bea,
0x3f76ba07,0x3e888e93,0x3f74484b,0x3e9920fe,0x3f718f57,0x3ea986c4,0x3f6e8ff8,0x3eb9bb1e,0x3f6b4b0c,0x3ec9b953,0x3f67c187,0x3ed97cb9,0x3f63f473,0x3ee900b7,0x3f5fe4e9,0x3ef840c8,
0x3f731447,0x3ea09ae5,0x3f6faf1b,0x3eb3dca5,0x3f6be858,0x3ec6d529,0x3f67c187,0x3ed97cb9,0x3f633c5a,0x3eebcbbb,0x3f5e5aa6,0x3efdbabb,0x3f591e6a,0x3f07a136,0x3f5389c7,0x3f102dd5,
0x3f6ed89e,0x3eb8442a,0x3f6a5ad9,0x3ece0bea,0x3f655e0b,0x3ee363fa,0x3f5fe4e9,0x3ef840c8,0x3f59f26a,0x3f064b82,0x3f5389c7,0x3f102dd5,0x3f4cae79,0x3f19c200,0x3f456439,0x3f2302d3,
0x3f6c835e,0x3ec3ef15,0x3f676bd8,0x3edae880,0x3f61c598,0x3ef15aea,0x3f5b941a,0x3f039c3d,0x3f54db31,0x3f0e39da,0x3f4d9f02,0x3f187fc0,0x3f45e403,0x3f226799,0x3f3daef9,0x3f2beb4a,
0x3f676bd8,0x3edae880,0x3f6106f2,0x3ef41f07,0x3f59f26a,0x3f064b82,0x3f5233c6,0x3f121eb0,0x3f49d112,0x3f1d7fd1,0x3f40d0da,0x3f286605,0x3f373a23,0x3f32c8c9,0x3f2d1469,0x3f3ca003,
0x3f61c598,0x3ef15aea,0x3f59f26a,0x3f064b82,0x3f514d3d,0x3f13682a,0x3f47de65,0x3f1ff6cb,0x3f3daef9,0x3f2beb4a,0x3f32c8c9,0x3f373a23,0x3f273656,0x3f41d870,0x3f1b02c6,0x3f4bbbf8,
0x3f5b941a,0x3f039c3d,0x3f5233c6,0x3f121eb0,0x3f47de65,0x3f1ff6cb,0x3f3ca003,0x3f2d1469,0x3f3085bb,0x3f396842,0x3f239da9,0x3f44e3f5,0x3f15f6d9,0x3f4f7a1f,0x3f07a136,0x3f591e6a,
0x3f6a09a7,0x3ecf7bca,0x3f644fac,0x3ee79a5d,0x3f5df6be,0x3eff17b2,0x3f570348,0x3f0af1b7,0x3f4f7a1f,0x3f15f6d9,0x3f476085,0x3f209393,0x3f3ebc1b,0x3f2ac082,0x3f3592e7,0x3f34768f,
0x3f64aa59,0x3ee63375,0x3f5d924d,0x3f003a06,0x3f55b993,0x3f0cead0,0x3f4d26fd,0x3f19210f,0x3f43e200,0x3f24d225,0x3f39f2ac,0x3f2ff3e6,0x3f2f61a5,0x3f3a7ca4,0x3f24381a,0x3f446337,
0x3f5ebe05,0x3efc5d27,0x3f5627fe,0x3f0c42c9,0x3f4cae79,0x3f19c200,0x3f425b89,0x3f269de3,0x3f373a23,0x3f32c8c9,0x3f2b561b,0x3f3e35c5,0x3f1ebc12,0x3f48d8b3,0x3f11796b,0x3f52a649,
0x3f584853,0x3f08f59b,0x3f4e1689,0x3f17de12,0x3f42de29,0x3f26050a,0x3f36ad7f,0x3f33587a,0x3f299415,0x3f3fc767,0x3f1ba299,0x3f4b41fa,0x3f0cead0,0x3f55b993,0x3efafef7,0x3f5f20db,
0x3f54db31,0x3f0e39da,0x3f49d112,0x3f1d7fd1,0x3f3daef9,0x3f2beb4a,0x3f3085bb,0x3f396842,0x3f226799,0x3f45e403,0x3f13682a,0x3f514d3d,0x3f039c3d,0x3f5b941a,0x3ee63375,0x3f64aa59,
0x3f4d9f02,0x3f187fc0,0x3f40d0da,0x3f286605,0x3f32c8c9,0x3f373a23,0x3f239da9,0x3f44e3f5,0x3f13682a,0x3f514d3d,0x3f0242b1,0x3f5c61c7,0x3ee0924f,0x3f660f88,0x3ebb31a0,0x3f6e46be,
0x3f45e403,0x3f226799,0x3f373a23,0x3f32c8c9,0x3f273656,0x3f41d870,0x3f15f6d9,0x3f4f7a1f,0x3f039c3d,0x3f5b941a,0x3ee0924f,0x3f660f88,0x3eb8442a,0x3f6ed89e,0x3e8e9a22,0x3f75dec6,
0x3f3daef9,0x3f2beb4a,0x3f2d1469,0x3f3ca003,0x3f1b02c6,0x3f4bbbf8,0x3f07a136,0x3f591e6a,0x3ee63375,0x3f64aa59,0x3ebb31a0,0x3f6e46be,0x3e8e9a22,0x3f75dec6,0x3e419b37,0x3f7b61fc,
0x3f514d3d,0x3f13682a,0x3f456439,0x3f2302d3,0x3f385216,0x3f31a81d,0x3f2a2a80,0x3f3f41fc,0x3f1b02c6,0x3f4bbbf8,0x3f0af1b7,0x3f570348,0x3ef41f07,0x3f6106f2,0x3ed0eb2a,0x3f69b7e4,
0x3f49d112,0x3f1d7fd1,0x3f3c17d9,0x3f2da859,0x3f2d1469,0x3f3ca003,0x3f1ce11f,0x3f4a4c87,0x3f0b9a6b,0x3f5695e5,0x3ef2bd43,0x3f61668a,0x3ecc9b8b,0x3f6aab7b,0x3ea5129f,0x3f725470,
0x3f41d870,0x3f273656,0x3f3238aa,0x3f37c655,0x3f212ff9,0x3f46e22a,0x3f0ee0db,0x3f546b3b,0x3ef6e0cb,0x3f604621,0x3ece0bea,0x3f6a5ad9,0x3ea395c5,0x3f7294f8,0x3e6fa8b2,0x3f78e3d6,
0x3f396842,0x3f3085bb,0x3f27ce61,0x3f4154e1,0x3f14b039,0x3f5064af,0x3f003a06,0x3f5d924d,0x3ed53641,0x3f68bf3c,0x3ea80b1f,0x3f71d19f,0x3e72b651,0x3f78b47b,0x3e1324ca,0x3f7d57de,
0x3f3504f3,0x3f3504f3,0x3f226799,0x3f45e403,0x3f0e39da,0x3f54db31,0x3ef15aea,0x3f61c598,0x3ec3ef15,0x3f6c835e,0x3e94a031,0x3f74fa0b,0x3e47c5c2,0x3f7b14be,0x3dc8bd36,0x3f7ec46d,
0x3f2beb4a,0x3f3daef9,0x3f173c07,0x3f4e8d90,0x3f00e7e4,0x3f5d2d53,0x3ed25a09,0x3f696591,0x3ea09ae5,0x3f731447,0x3e5a3997,0x3f7a1e84,0x3de1bc2e,0x3f7e70b0,0x3bc90f88,0x3f7ffec4,
0x3f226799,0x3f45e403,0x3f0b9a6b,0x3f5695e5,0x3ee63375,0x3f64aa59,0x3eb263ef,0x3f6ff573,0x3e78cfcc,0x3f7853f8,0x3e09cf86,0x3f7dabcc,0x3cc90ab0,0x3f7fec43,0xbdafb680,0x3f7f0e58,
0x3f187fc0,0x3f4d9f02,0x3eff17b2,0x3f5df6be,0x3ec9b953,0x3f6b4b0c,0x3e919ddd,0x3f756d97,0x3e2f10a2,0x3f7c3b28,0x3d621469,0x3f7f9c18,0xbd7b2b74,0x3f7f84ab,0xbe354098,0x3f7bf531,
0x3f3085bb,0x3f396842,0x3f1ce11f,0x3f4a4c87,0x3f07a136,0x3f591e6a,0x3ee1fb6a,0x3f65b710,0x3eb263ef,0x3f6ff573,0x3e80f8c0,0x3f77beb7,0x3e1c76de,0x3f7cfe73,0x3d55880e,0x3f7fa6e3,
0x3f273656,0x3f41d870,0x3f11796b,0x3f52a649,0x3ef41f07,0x3f6106f2,0x3ec27b55,0x3f6cd007,0x3e8e9a22,0x3f75dec6,0x3e3228d4,0x3f7c187a,0x3d8a200a,0x3f7f6ac7,0xbd2351cb,0x3f7fcbe2,
0x3f1d7fd1,0x3f49d112,0x3f05a02c,0x3f5a5ba0,0x3ed8106b,0x3f6816a8,0x3ea21887,0x3f72d4eb,0x3e541501,0x3f7a7302,0x3dc27c39,0x3f7ed7d4,0xbc96c9b6,0x3f7ff4e6,0xbe06b26e,0x3f7dc68c,
0x3f13682a,0x3f514d3d,0x3ef2bd43,0x3f61668a,0x3ebb31a0,0x3f6e46be,0x3e80f8c0,0x3f77beb7,0x3e09cf86,0x3f7dabcc,0x3c7b514b,0x3f7ff84a,0xbdd53db9,0x3f7e9bc9,0xbe636c83,0x3f799b43,
0x3f0e39da,0x3f54db31,0x3ee63375,0x3f64aa59,0x3eac7cd4,0x3f710908,0x3e605c13,0x3f79c79d,0x3dc8bd36,0x3f7ec46d,0xbcc90ab0,0x3f7fec43,0xbe164083,0x3f7d3aac,0xbe888e93,0x3f76ba07,
0x3f039c3d,0x3f5b941a,0x3ecc9b8b,0x3f6aab7b,0x3e8e9a22,0x3f75dec6,0x3e1c76de,0x3f7cfe73,0x3cc90ab0,0x3f7fec43,0xbdd53db9,0x3f7e9bc9,0xbe6c9a7f,0x3f791298,0xbeb554ec,0x3f6f6830,
0x3ef15aea,0x3f61c598,0x3eb263ef,0x3f6ff573,0x3e605c13,0x3f79c79d,0x3dafb680,0x3f7f0e58,0xbd48fb30,0x3f7fb10f,0xbe3b6ecf,0x3f7baccd,0xbea09ae5,0x3f731447,0xbee0924f,0x3f660f88,
0x3edae880,0x3f676bd8,0x3e97a117,0x3f748422,0x3e22abb6,0x3f7cbfc9,0x3c96c9b6,0x3f7ff4e6,0xbdfab273,0x3f7e1324,0xbe8586ce,0x3f772417,0xbec9b953,0x3f6b4b0c,0xbf04f484,0x3f5ac450,
0x3f08f59b,0x3f584853,0x3ed97cb9,0x3f67c187,0x3e9d9e78,0x3f73913f,0x3e3e853e,0x3f7b87b2,0x3d7b2b74,0x3f7f84ab,0xbd83db0a,0x3f7f7808,0xbe419b37,0x3f7b61fc,0xbe9f1cdf,0x3f73530e,
0x3efc5d27,0x3f5ebe05,0x3ebf926f,0x3f6d67a1,0x3e7ee6e1,0x3f77f110,0x3df475c0,0x3f7e2b72,0xbc490e90,0x3f7ffb11,0xbe1324ca,0x3f7d57de,0xbe8b9507,0x3f764d97,0xbecb2aae,0x3f6afb8c,
0x3ee63375,0x3f64aa59,0x3ea5129f,0x3f725470,0x3e419b37,0x3f7b61fc,0x3d55880e,0x3f7fa6e3,0xbdafb680,0x3f7f0e58,0xbe636c83,0x3f799b43,0xbeb554ec,0x3f6f6830,0xbef58035,0x3f60a6cf,
0x3ecf7bca,0x3f6a09a7,0x3e8a11f7,0x3f76841b,0x3e039502,0x3f7de0b1,0xbc7b514b,0x3f7ff84a,0xbe22abb6,0x3f7cbfc9,0xbe9920fe,0x3f74484b,0xbeddbe79,0x3f66becc,0xbf0ee0db,0x3f546b3b,
0x3ec3ef15,0x3f6c835e,0x3e78cfcc,0x3f7853f8,0x3dc8bd36,0x3f7ec46d,0xbd48fb30,0x3f7fb10f,0xbe47c5c2,0x3f7b14be,0xbeac7cd4,0x3f710908,0xbef15aea,0x3f61c598,0xbf187fc0,0x3f4d9f02,
0x3eac7cd4,0x3f710908,0x3e419b37,0x3f7b61fc,0x3d16c32c,0x3f7fd397,0xbdee3876,0x3f7e4323,0xbe888e93,0x3f76ba07,0xbed25a09,0x3f696591,0xbf0b9a6b,0x3f5695e5,0xbf2ac082,0x3f3ebc1b,
0x3e94a031,0x3f74fa0b,0x3e09cf86,0x3f7dabcc,0xbcc90ab0,0x3f7fec43,0xbe3b6ecf,0x3f7baccd,0xbeac7cd4,0x3f710908,0xbef6e0cb,0x3f604621,0xbf1d7fd1,0x3f49d112,0xbf3b8f3b,0x3f2e3bde,
0x3e78cfcc,0x3f7853f8,0x3da3308c,0x3f7f2f9d,0xbdafb680,0x3f7f0e58,0xbe7ee6e1,0x3f77f110,0xbecf7bca,0x3f6a09a7,0xbf0cead0,0x3f55b993,0xbf2e3bde,0x3f3b8f3b,0xbf4ac77f,0x3f1c420c,
0x3eb8442a,0x3f6ed89e,0x3e5d4b1a,0x3f79f35e,0x3d8a200a,0x3f7f6ac7,0xbda973ba,0x3f7f1f49,0xbe6c9a7f,0x3f791298,0xbebf926f,0x3f6d67a1,0xbf0242b1,0x3f5c61c7,0xbf21cbfb,0x3f466354,
0x3ea09ae5,0x3f731447,0x3e25c58c,0x3f7c9f8a,0x3bc90f88,0x3f7ffec4,0xbe195be0,0x3f7d1cdd,0xbe9aa086,0x3f740bdd,0xbee4cbfe,0x3f650479,0xbf14b039,0x3f5064af,0xbf33587a,0x3f36ad7f,
0x3e888e93,0x3f76ba07,0x3ddb7d37,0x3f7e868b,0xbd621469,0x3f7f9c18,0xbe5d4b1a,0x3f79f35e,0xbebe1d4a,0x3f6db293,0xbf044889,0x3f5b2c79,0xbf26050a,0x3f42de29,0xbf436051,0x3f256bcb,
0x3e605c13,0x3f79c79d,0x3d55880e,0x3f7fa6e3,0xbdee3876,0x3f7e4323,0xbe901c2c,0x3f75a67b,0xbee0924f,0x3f660f88,0xbf1553b7,0x3f4fefa8,0xbf36206c,0x3f33e7bc,0xbf51c0c2,0x3f12c39a,
0x3e47c5c2,0x3f7b14be,0x3cc90ab0,0x3f7fec43,0xbe164083,0x3f7d3aac,0xbea09ae5,0x3f731447,0xbef15aea,0x3f61c598,0xbf1d7fd1,0x3f49d112,0xbf3daef9,0x3f2beb4a,0xbf584853,0x3f08f59b,
0x3e164083,0x3f7d3aac,0xbcfb49ba,0x3f7fe129,0xbe541501,0x3f7a7302,0xbec1071e,0x3f6d1c1d,0xbf08f59b,0x3f584853,0xbf2d1469,0x3f3ca003,0xbf4bbbf8,0x3f1b02c6,0xbf63f473,0x3ee900b7,
0x3dc8bd36,0x3f7ec46d,0xbdafb680,0x3f7f0e58,0xbe888e93,0x3f76ba07,0xbee0924f,0x3f660f88,0xbf187fc0,0x3f4d9f02,0xbf3b8f3b,0x3f2e3bde,0xbf584853,0x3f08f59b,0xbf6db293,0x3ebe1d4a,
0x3d48fb30,0x3f7fb10f,0xbe1008b7,0x3f7d7474,0xbea68f12,0x3f721352,0xbeff17b2,0x3f5df6be,0xbf273656,0x3f41d870,0xbf48d8b3,0x3f1ebc12,0xbf633c5a,0x3eebcbbb,0xbf756d97,0x3e919ddd,
0x3e2f10a2,0x3f7c3b28,0xbb490fc6,0x3f7fffb1,0xbe354098,0x3f7bf531,0xbeb0eacb,0x3f703b37,0xbf00e7e4,0x3f5d2d53,0xbf256bcb,0x3f436051,0xbf44e3f5,0x3f239da9,0xbf5e5aa6,0x3efdbabb,
0x3dfab273,0x3f7e1324,0xbd6ea038,0x3f7f90b1,0xbe72b651,0x3f78b47b,0xbed0eb2a,0x3f69b7e4,0xbf10d3cd,0x3f531849,0xbf34768f,0x3f3592e7,0xbf5233c6,0x3f121eb0,0xbf6912ae,0x3ed3c867,
0x3d96a905,0x3f7f4e6d,0xbde7fa9a,0x3f7e5a38,0xbe97a117,0x3f748422,0xbeeff7fb,0x3f62241a,0xbf1ff6cb,0x3f47de65,0xbf425b89,0x3f269de3,0xbf5df6be,0x3eff17b2,0xbf71d19f,0x3ea80b1f,
0x3cc90ab0,0x3f7fec43,0xbe2bf804,0x3f7c5d3a,0xbeb554ec,0x3f6f6830,0xbf06f686,0x3f5988ad,0xbf2e3bde,0x3f3b8f3b,0xbf4f0417,0x3f16999f,0xbf6816a8,0x3ed8106b,0xbf788486,0x3e75c35a,
0x3f800000,0,0x3f800000,0,0x3f800000,0,0x3f800000,0,0x3f800000,0,0x3f800000,0,0x3f800000,0,0x3f800000,0,
0x3f7ec46d,0x3dc8bd36,0x3f7e9bc9,0x3dd53db9,0x3f7e70b0,0x3de1bc2e,0x3f7e4323,0x3dee3876,0x3f7e1324,0x3dfab273,0x3f7de0b1,0x3e039502,0x3f7dabcc,0x3e09cf86,0x3f7d7474,0x3e1008b7,
0x3f7b14be,0x3e47c5c2,0x3f7a7302,0x3e541501,0x3f79c79d,0x3e605c13,0x3f791298,0x3e6c9a7f,0x3f7853f8,0x3e78cfcc,0x3f778bc5,0x3e827dc0,0x3f76ba07,0x3e888e93,0x3f75dec6,0x3e8e9a22,
0x3f74fa0b,0x3e94a031,0x3f73913f,0x3e9d9e78,0x3f721352,0x3ea68f12,0x3f708066,0x3eaf713a,0x3f6ed89e,0x3eb8442a,0x3f6d1c1d,0x3ec1071e,0x3f6b4b0c,0x3ec9b953,0x3f696591,0x3ed25a09,
0x3f7fb10f,0x3d48fb30,0x3f7fa6e3,0x3d55880e,0x3f7f9c18,0x3d621469,0x3f7f90b1,0x3d6ea038,0x3f7f84ab,0x3d7b2b74,0x3f7f7808,0x3d83db0a,0x3f7f6ac7,0x3d8a200a,0x3f7f5ce9,0x3d9064b4,
0x3f7d3aac,0x3e164083,0x3f7cdf6c,0x3e1f917b,0x3f7c7eb0,0x3e28defc,0x3f7c187a,0x3e3228d4,0x3f7baccd,0x3e3b6ecf,0x3f7b3bab,0x3e44b0b9,0x3f7ac516,0x3e4dee60,0x3f7a4910,0x3e57278f,
0x3f7853f8,0x3e78cfcc,0x3f77583a,0x3e840270,0x3f764d97,0x3e8b9507,0x3f75341d,0x3e931f35,0x3f740bdd,0x3e9aa086,0x3f72d4eb,0x3ea21887,0x3f718f57,0x3ea986c4,0x3f703b37,0x3eb0eacb,
0x3f710908,0x3eac7cd4,0x3f6f20b0,0x3eb6ccc3,0x3f6d1c1d,0x3ec1071e,0x3f6afb8c,0x3ecb2aae,0x3f68bf3c,0x3ed53641,0x3f666771,0x3edf28a9,0x3f63f473,0x3ee900b7,0x3f61668a,0x3ef2bd43,
0x3f6c835e,0x3ec3ef15,0x3f6a09a7,0x3ecf7bca,0x3f676bd8,0x3edae880,0x3f64aa59,0x3ee63375,0x3f61c598,0x3ef15aea,0x3f5ebe05,0x3efc5d27,0x3f5b941a,0x3f039c3d,0x3f584853,0x3f08f59b,
0x3f61c598,0x3ef15aea,0x3f5df6be,0x3eff17b2,0x3f59f26a,0x3f064b82,0x3f55b993,0x3f0cead0,0x3f514d3d,0x3f13682a,0x3f4cae79,0x3f19c200,0x3f47de65,0x3f1ff6cb,0x3f42de29,0x3f26050a,
0x3f54db31,0x3f0e39da,0x3f4f7a1f,0x3f15f6d9,0x3f49d112,0x3f1d7fd1,0x3f43e200,0x3f24d225,0x3f3daef9,0x3f2beb4a,0x3f373a23,0x3f32c8c9,0x3f3085bb,0x3f396842,0x3f299415,0x3f3fc767,
0x3f45e403,0x3f226799,0x3f3ebc1b,0x3f2ac082,0x3f373a23,0x3f32c8c9,0x3f2f61a5,0x3f3a7ca4,0x3f273656,0x3f41d870,0x3f1ebc12,0x3f48d8b3,0x3f15f6d9,0x3f4f7a1f,0x3f0cead0,0x3f55b993,
0x3f676bd8,0x3edae880,0x3f644fac,0x3ee79a5d,0x3f6106f2,0x3ef41f07,0x3f5d924d,0x3f003a06,0x3f59f26a,0x3f064b82,0x3f5627fe,0x3f0c42c9,0x3f5233c6,0x3f121eb0,0x3f4e1689,0x3f17de12,
0x3f5b941a,0x3f039c3d,0x3f570348,0x3f0af1b7,0x3f5233c6,0x3f121eb0,0x3f4d26fd,0x3f19210f,0x3f47de65,0x3f1ff6cb,0x3f425b89,0x3f269de3,0x3f3ca003,0x3f2d1469,0x3f36ad7f,0x3f33587a,
0x3f4d9f02,0x3f187fc0,0x3f476085,0x3f209393,0x3f40d0da,0x3f286605,0x3f39f2ac,0x3f2ff3e6,0x3f32c8c9,0x3f373a23,0x3f2b561b,0x3f3e35c5,0x3f239da9,0x3f44e3f5,0x3f1ba299,0x3f4b41fa,
0x3f3daef9,0x3f2beb4a,0x3f3592e7,0x3f34768f,0x3f2d1469,0x3f3ca003,0x3f24381a,0x3f446337,0x3f1b02c6,0x3f4bbbf8,0x3f11796b,0x3f52a649,0x3f07a136,0x3f591e6a,0x3efafef7,0x3f5f20db,
0x3f3504f3,0x3f3504f3,0x3f2beb4a,0x3f3daef9,0x3f226799,0x3f45e403,0x3f187fc0,0x3f4d9f02,0x3f0e39da,0x3f54db31,0x3f039c3d,0x3f5b941a,0x3ef15aea,0x3f61c598,0x3edae880,0x3f676bd8,
0x3f226799,0x3f45e403,0x3f173c07,0x3f4e8d90,0x3f0b9a6b,0x3f5695e5,0x3eff17b2,0x3f5df6be,0x3ee63375,0x3f64aa59,0x3ecc9b8b,0x3f6aab7b,0x3eb263ef,0x3f6ff573,0x3e97a117,0x3f748422,
0x3f0e39da,0x3f54db31,0x3f00e7e4,0x3f5d2d53,0x3ee63375,0x3f64aa59,0x3ec9b953,0x3f6b4b0c,0x3eac7cd4,0x3f710908,0x3e8e9a22,0x3f75dec6,0x3e605c13,0x3f79c79d,0x3e22abb6,0x3f7cbfc9,
0x3ef15aea,0x3f61c598,0x3ed25a09,0x3f696591,0x3eb263ef,0x3f6ff573,0x3e919ddd,0x3f756d97,0x3e605c13,0x3f79c79d,0x3e1c76de,0x3f7cfe73,0x3dafb680,0x3f7f0e58,0x3c96c9b6,0x3f7ff4e6,
0x3f2beb4a,0x3f3daef9,0x3f21cbfb,0x3f466354,0x3f173c07,0x3f4e8d90,0x3f0c42c9,0x3f5627fe,0x3f00e7e4,0x3f5d2d53,0x3eea6681,0x3f6398ac,0x3ed25a09,0x3f696591,0x3eb9bb1e,0x3f6e8ff8,
0x3f187fc0,0x3f4d9f02,0x3f0c42c9,0x3f5627fe,0x3eff17b2,0x3f5df6be,0x3ee4cbfe,0x3f650479,0x3ec9b953,0x3f6b4b0c,0x3eadf73c,0x3f70c501,0x3e919ddd,0x3f756d97,0x3e698bba,0x3f7940c0,
0x3f039c3d,0x3f5b941a,0x3eea6681,0x3f6398ac,0x3ecc9b8b,0x3f6aab7b,0x3eadf73c,0x3f70c501,0x3e8e9a22,0x3f75dec6,0x3e5d4b1a,0x3f79f35e,0x3e1c76de,0x3f7cfe73,0x3db5f8da,0x3f7efcc9,
0x3edae880,0x3f676bd8,0x3eb9bb1e,0x3f6e8ff8,0x3e97a117,0x3f748422,0x3e698bba,0x3f7940c0,0x3e22abb6,0x3f7cbfc9,0x3db5f8da,0x3f7efcc9,0x3c96c9b6,0x3f7ff4e6,0xbd55880e,0x3f7fa6e3,
0x3ec3ef15,0x3f6c835e,0x3ea09ae5,0x3f731447,0x3e78cfcc,0x3f7853f8,0x3e2f10a2,0x3f7c3b28,0x3dc8bd36,0x3f7ec46d,0x3cc90ab0,0x3f7fec43,0xbd48fb30,0x3f7fb10f,0xbdfab273,0x3f7e1324,
0x3e94a031,0x3f74fa0b,0x3e5a3997,0x3f7a1e84,0x3e09cf86,0x3f7dabcc,0x3d621469,0x3f7f9c18,0xbcc90ab0,0x3f7fec43,0xbdd53db9,0x3f7e9bc9,0xbe3b6ecf,0x3f7baccd,0xbe8586ce,0x3f772417,
0x3e47c5c2,0x3f7b14be,0x3de1bc2e,0x3f7e70b0,0x3cc90ab0,0x3f7fec43,0xbd7b2b74,0x3f7f84ab,0xbe164083,0x3f7d3aac,0xbe6c9a7f,0x3f791298,0xbea09ae5,0x3f731447,0xbec9b953,0x3f6b4b0c,
0x3dc8bd36,0x3f7ec46d,0x3bc90f88,0x3f7ffec4,0xbdafb680,0x3f7f0e58,0xbe354098,0x3f7bf531,0xbe888e93,0x3f76ba07,0xbeb554ec,0x3f6f6830,0xbee0924f,0x3f660f88,0xbf04f484,0x3f5ac450,
0x3eac7cd4,0x3f710908,0x3e870ada,0x3f76ef5b,0x3e419b37,0x3f7b61fc,0x3de7fa9a,0x3f7e5a38,0x3d16c32c,0x3f7fd397,0xbd2351cb,0x3f7fcbe2,0xbdee3876,0x3f7e4323,0xbe44b0b9,0x3f7b3bab,
0x3e78cfcc,0x3f7853f8,0x3e25c58c,0x3f7c9f8a,0x3da3308c,0x3f7f2f9d,0xbb490fc6,0x3f7fffb1,0xbdafb680,0x3f7f0e58,0xbe2bf804,0x3f7c5d3a,0xbe7ee6e1,0x3f77f110,0xbea80b1f,0x3f71d19f,
0x3e164083,0x3f7d3aac,0x3d6ea038,0x3f7f90b1,0xbcfb49ba,0x3f7fe129,0xbdf475c0,0x3f7e2b72,0xbe541501,0x3f7a7302,0xbe9620d2,0x3f74bf62,0xbec1071e,0x3f6d1c1d,0xbeea6681,0x3f6398ac,
0x3d48fb30,0x3f7fb10f,0xbd3c6dd5,0x3f7fba9e,0xbe1008b7,0x3f7d7474,0xbe6fa8b2,0x3f78e3d6,0xbea68f12,0x3f721352,0xbed3c867,0x3f6912ae,0xbeff17b2,0x3f5df6be,0xbf140c5f,0x3f50d937,
0,0x3f800000,0xbdc8bd36,0x3f7ec46d,0xbe47c5c2,0x3f7b14be,0xbe94a031,0x3f74fa0b,0xbec3ef15,0x3f6c835e,0xbef15aea,0x3f61c598,0xbf0e39da,0x3f54db31,0xbf226799,0x3f45e403,
0xbdc8bd36,0x3f7ec46d,0xbe4dee60,0x3f7ac516,0xbe9aa086,0x3f740bdd,0xbecc9b8b,0x3f6aab7b,0xbefc5d27,0x3f5ebe05,0xbf14b039,0x3f5064af,0xbf299415,0x3f3fc767,0xbf3ca003,0x3f2d1469,
0xbe47c5c2,0x3f7b14be,0xbe9aa086,0x3f740bdd,0xbecf7bca,0x3f6a09a7,0xbf00e7e4,0x3f5d2d53,0xbf187fc0,0x3f4d9f02,0xbf2e3bde,0x3f3b8f3b,0xbf41d870,0x3f273656,0xbf531849,0x3f10d3cd,
0xbe94a031,0x3f74fa0b,0xbecc9b8b,0x3f6aab7b,0xbf00e7e4,0x3f5d2d53,0xbf19c200,0x3f4cae79,0xbf3085bb,0x3f396842,0xbf44e3f5,0x3f239da9,0xbf5695e5,0x3f0b9a6b,0xbf655e0b,0x3ee363fa,
0xbd48fb30,0x3f7fb10f,0xbe195be0,0x3f7d1cdd,0xbe7ee6e1,0x3f77f110,0xbeb0eacb,0x3f703b37,0xbee0924f,0x3f660f88,0xbf06f686,0x3f5988ad,0xbf1c420c,0x3f4ac77f,0xbf2ff3e6,0x3f39f2ac,
0xbe164083,0x3f7d3aac,0xbe80f8c0,0x3f77beb7,0xbeb554ec,0x3f6f6830,0xbee79a5d,0x3f644fac,0xbf0b9a6b,0x3f5695e5,0xbf21cbfb,0x3f466354,0xbf36206c,0x3f33e7bc,0xbf485bca,0x3f1f599f,
0xbe78cfcc,0x3f7853f8,0xbeb3dca5,0x3f6faf1b,0xbee900b7,0x3f63f473,0xbf0d9281,0x3f554aa4,0xbf24d225,0x3f43e200,0xbf39f2ac,0x3f2ff3e6,0xbf4cae79,0x3f19c200,0xbf5cc7d1,0x3f019573,
0xbeac7cd4,0x3f710908,0xbee4cbfe,0x3f650479,0xbf0cead0,0x3f55b993,0xbf256bcb,0x3f436051,0xbf3b8f3b,0x3f2e3bde,0xbf4f0417,0x3f16999f,0xbf5f8327,0x3ef9a02d,0xbf6cd007,0x3ec27b55,
0xbec3ef15,0x3f6c835e,0xbefc5d27,0x3f5ebe05,0xbf187fc0,0x3f4d9f02,0xbf3085bb,0x3f396842,0xbf45e403,0x3f226799,0xbf584853,0x3f08f59b,0xbf676bd8,0x3edae880,0xbf731447,0x3ea09ae5,
0xbef15aea,0x3f61c598,0xbf14b039,0x3f5064af,0xbf2e3bde,0x3f3b8f3b,0xbf44e3f5,0x3f239da9,0xbf584853,0x3f08f59b,0xbf6816a8,0x3ed8106b,0xbf740bdd,0x3e9aa086,0xbf7bf531,0x3e354098,
0xbf0e39da,0x3f54db31,0xbf299415,0x3f3fc767,0xbf41d870,0x3f273656,0xbf5695e5,0x3f0b9a6b,0xbf676bd8,0x3edae880,0xbf740bdd,0x3e9aa086,0xbf7c3b28,0x3e2f10a2,0xbf7fd397,0x3d16c32c,
0xbf226799,0x3f45e403,0xbf3ca003,0x3f2d1469,0xbf531849,0x3f10d3cd,0xbf655e0b,0x3ee363fa,0xbf731447,0x3ea09ae5,0xbf7bf531,0x3e354098,0xbf7fd397,0x3d16c32c,0xbf7e9bc9,0xbdd53db9,
0xbedae880,0x3f676bd8,0xbf099f4e,0x3f57dc7f,0xbf239da9,0x3f44e3f5,0xbf3b0629,0x3f2ecef7,0xbf4f7a1f,0x3f15f6d9,0xbf60a6cf,0x3ef58035,0xbf6e46be,0x3ebb31a0,0xbf7822d1,0x3e7bdba4,
0xbf039c3d,0x3f5b941a,0xbf1f599f,0x3f485bca,0xbf385216,0x3f31a81d,0xbf4e1689,0x3f17de12,0xbf604621,0x3ef6e0cb,0xbf6e8ff8,0x3eb9bb1e,0xbf78b47b,0x3e72b651,0xbf7e868b,0x3ddb7d37,
0xbf187fc0,0x3f4d9f02,0xbf33587a,0x3f36ad7f,0xbf4ac77f,0x3f1c420c,0xbf5e5aa6,0x3efdbabb,0xbf6db293,0x3ebe1d4a,0xbf788486,0x3e75c35a,0xbf7e9bc9,0x3dd53db9,0xbf7fdaaf,0xbd0a342f,
0xbf2beb4a,0x3f3daef9,0xbf456439,0x3f2302d3,0xbf5ac450,0x3f04f484,0xbf6b99fb,0x3ec8477c,0xbf778bc5,0x3e827dc0,0xbf7e5a38,0x3de7fa9a,0xbf7fe129,0xbcfb49ba,0xbf7c187a,0xbe3228d4,
0xbf3504f3,0x3f3504f3,0xbf4d9f02,0x3f187fc0,0xbf61c598,0x3ef15aea,0xbf710908,0x3eac7cd4,0xbf7b14be,0x3e47c5c2,0xbf7fb10f,0x3d48fb30,0xbf7ec46d,0xbdc8bd36,0xbf7853f8,0xbe78cfcc,
0xbf45e403,0x3f226799,0xbf5c61c7,0x3f0242b1,0xbf6db293,0x3ebe1d4a,0xbf796e4e,0x3e667c66,0xbf7f4e6d,0x3d96a905,0xbf7f2f9d,0xbda3308c,0xbf791298,0xbe6c9a7f,0xbf6d1c1d,0xbec1071e,
0xbf54db31,0x3f0e39da,0xbf68bf3c,0x3ed53641,0xbf76ba07,0x3e888e93,0xbf7e70b0,0x3de1bc2e,0xbf7fb10f,0xbd48fb30,0xbf7a7302,0xbe541501,0xbf6ed89e,0xbeb8442a,0xbf5d2d53,0xbf00e7e4,
0xbf61c598,0x3ef15aea,0xbf7294f8,0x3ea395c5,0xbf7cbfc9,0x3e22abb6,0xbf7ffec4,0xbbc90f88,0xbf7c3b28,0xbe2f10a2,0xbf718f57,0xbea986c4,0xbf604621,0xbef6e0cb,0xbf48d8b3,0xbf1ebc12,
0xbf3daef9,0x3f2beb4a,0xbf554aa4,0x3f0d9281,0xbf6816a8,0x3ed8106b,0xbf75a67b,0x3e901c2c,0xbf7dabcc,0x3e09cf86,0xbf7ff84a,0xbc7b514b,0xbf7c7eb0,0xbe28defc,0xbf73530e,0xbe9f1cdf,
0xbf4d9f02,0x3f187fc0,0xbf62df7b,0x3eed3063,0xbf7294f8,0x3ea395c5,0xbf7c5d3a,0x3e2bf804,0xbf7ffb11,0x3c490e90,0xbf7d57de,0xbe1324ca,0xbf748422,0xbe97a117,0xbf65b710,0xbee1fb6a,
0xbf5b941a,0x3f039c3d,0xbf6dfcf2,0x3ebca7af,0xbf7a1e84,0x3e5a3997,0xbf7fa6e3,0x3d55880e,0xbf7e70b0,0xbde1bc2e,0xbf76841b,0xbe8a11f7,0xbf6816a8,0xbed8106b,0xbf5389c7,0xbf102dd5,
0xbf676bd8,0x3edae880,0xbf76841b,0x3e8a11f7,0xbf7e9bc9,0x3dd53db9,0xbf7f7808,0xbd83db0a,0xbf791298,0xbe6c9a7f,0xbf6b99fb,0xbec8477c,0xbf577026,0xbf0a48ad,0xbf3d27b8,0xbf2c800f,
0xbf6c835e,0x3ec3ef15,0xbf79c79d,0x3e605c13,0xbf7fb10f,0x3d48fb30,0xbf7e1324,0xbdfab273,0xbf74fa0b,0xbe94a031,0xbf64aa59,0xbee63375,0xbf4d9f02,0xbf187fc0,0xbf3085bb,0xbf396842,
0xbf74fa0b,0x3e94a031,0xbf7e4323,0x3dee3876,0xbf7f84ab,0xbd7b2b74,0xbf78b47b,0xbe72b651,0xbf6a09a7,0xbecf7bca,0xbf53fac3,0xbf0f8784,0xbf373a23,0xbf32c8c9,0xbf14b039,0xbf5064af,
0xbf7b14be,0x3e47c5c2,0xbf7ffb11,0x3c490e90,0xbf7c3b28,0xbe2f10a2,0xbf6ff573,0xbeb263ef,0xbf5b941a,0xbf039c3d,0xbf3fc767,0xbf299415,0xbf1d7fd1,0xbf49d112,0xbeebcbbb,0xbf633c5a,
0xbf7ec46d,0x3dc8bd36,0xbf7eea9d,0xbdbc3ac3,0xbf75dec6,0xbe8e9a22,0xbf63f473,0xbee900b7,0xbf49d112,0xbf1d7fd1,0xbf286605,0xbf40d0da,0xbf00e7e4,0xbf5d2d53,0xbea986c4,0xbf718f57,
0xbf710908,0x3eac7cd4,0xbf7c5d3a,0x3e2bf804,0xbf7ffec4,0xbbc90f88,0xbf7bd14d,0xbe3857ec,0xbf6ff573,0xbeb263ef,0xbf5cc7d1,0xbf019573,0xbf42de29,0xbf26050a,0xbf2302d3,0xbf456439,
0xbf7853f8,0x3e78cfcc,0xbf7f7808,0x3d83db0a,0xbf7e4323,0xbdee3876,0xbf74bf62,0xbe9620d2,0xbf633c5a,0xbeebcbbb,0xbf4a4c87,0xbf1ce11f,0xbf2ac082,0xbf3ebc1b,0xbf05a02c,0xbf5a5ba0,
0xbf7d3aac,0x3e164083,0xbf7fcbe2,0xbd2351cb,0xbf796e4e,0xbe667c66,0xbf6a5ad9,0xbece0bea,0xbf531849,0xbf10d3cd,0xbf34768f,0xbf3592e7,0xbf0f8784,0xbf53fac3,0xbecb2aae,0xbf6afb8c,
0xbf7fb10f,0x3d48fb30,0xbf7d57de,0xbe1324ca,0xbf718f57,0xbea986c4,0xbf5cc7d1,0xbf019573,0xbf3fc767,0xbf299415,0xbf1ba299,0xbf4b41fa,0xbee363fa,0xbf655e0b,0xbe870ada,0xbf76ef5b,
0x3f800000,0,0x3f800000,0,0x3f800000,0,0x3f800000,0,0x3f800000,0,0x3f800000,0,0x3f800000,0,0x3f800000,0,
0x3f7d3aac,0x3e164083,0x3f7cfe73,0x3e1c76de,0x3f7cbfc9,0x3e22abb6,0x3f7c7eb0,0x3e28defc,0x3f7c3b28,0x3e2f10a2,0x3f7bf531,0x3e354098,0x3f7baccd,0x3e3b6ecf,0x3f7b61fc,0x3e419b37,
0x3f74fa0b,0x3e94a031,0x3f740bdd,0x3e9aa086,0x3f731447,0x3ea09ae5,0x3f721352,0x3ea68f12,0x3f710908,0x3eac7cd4,0x3f6ff573,0x3eb263ef,0x3f6ed89e,0x3eb8442a,0x3f6db293,0x3ebe1d4a,
0x3f676bd8,0x3edae880,0x3f655e0b,0x3ee363fa,0x3f633c5a,0x3eebcbbb,0x3f6106f2,0x3ef41f07,0x3f5ebe05,0x3efc5d27,0x3f5c61c7,0x3f0242b1,0x3f59f26a,0x3f064b82,0x3f577026,0x3f0a48ad,
0x3f7f4e6d,0x3d96a905,0x3f7f3f54,0x3d9cecf9,0x3f7f2f9d,0x3da3308c,0x3f7f1f49,0x3da973ba,0x3f7f0e58,0x3dafb680,0x3f7efcc9,0x3db5f8da,0x3f7eea9d,0x3dbc3ac3,0x3f7ed7d4,0x3dc27c39,
0x3f79c79d,0x3e605c13,0x3f7940c0,0x3e698bba,0x3f78b47b,0x3e72b651,0x3f7822d1,0x3e7bdba4,0x3f778bc5,0x3e827dc0,0x3f76ef5b,0x3e870ada,0x3f764d97,0x3e8b9507,0x3f75a67b,0x3e901c2c,
0x3f6ed89e,0x3eb8442a,0x3f6d67a1,0x3ebf926f,0x3f6be858,0x3ec6d529,0x3f6a5ad9,0x3ece0bea,0x3f68bf3c,0x3ed53641,0x3f671599,0x3edc53c1,0x3f655e0b,0x3ee363fa,0x3f6398ac,0x3eea6681,
0x3f5ebe05,0x3efc5d27,0x3f5bfb34,0x3f02ef9f,0x3f591e6a,0x3f07a136,0x3f5627fe,0x3f0c42c9,0x3f531849,0x3f10d3cd,0x3f4fefa8,0x3f1553b7,0x3f4cae79,0x3f19c200,0x3f495521,0x3f1e1e22,
0x3f54db31,0x3f0e39da,0x3f514d3d,0x3f13682a,0x3f4d9f02,0x3f187fc0,0x3f49d112,0x3f1d7fd1,0x3f45e403,0x3f226799,0x3f41d870,0x3f273656,0x3f3daef9,0x3f2beb4a,0x3f396842,0x3f3085bb,
0x3f3daef9,0x3f2beb4a,0x3f385216,0x3f31a81d,0x3f32c8c9,0x3f373a23,0x3f2d1469,0x3f3ca003,0x3f273656,0x3f41d870,0x3f212ff9,0x3f46e22a,0x3f1b02c6,0x3f4bbbf8,0x3f14b039,0x3f5064af,
0x3f226799,0x3f45e403,0x3f1b02c6,0x3f4bbbf8,0x3f13682a,0x3f514d3d,0x3f0b9a6b,0x3f5695e5,0x3f039c3d,0x3f5b941a,0x3ef6e0cb,0x3f604621,0x3ee63375,0x3f64aa59,0x3ed53641,0x3f68bf3c,
0x3f039c3d,0x3f5b941a,0x3ef41f07,0x3f6106f2,0x3ee0924f,0x3f660f88,0x3ecc9b8b,0x3f6aab7b,0x3eb8442a,0x3f6ed89e,0x3ea395c5,0x3f7294f8,0x3e8e9a22,0x3f75dec6,0x3e72b651,0x3f78b47b,
0x3f49d112,0x3f1d7fd1,0x3f456439,0x3f2302d3,0x3f40d0da,0x3f286605,0x3f3c17d9,0x3f2da859,0x3f373a23,0x3f32c8c9,0x3f3238aa,0x3f37c655,0x3f2d1469,0x3f3ca003,0x3f27ce61,0x3f4154e1,
0x3f3085bb,0x3f396842,0x3f2a2a80,0x3f3f41fc,0x3f239da9,0x3f44e3f5,0x3f1ce11f,0x3f4a4c87,0x3f15f6d9,0x3f4f7a1f,0x3f0ee0db,0x3f546b3b,0x3f07a136,0x3f591e6a,0x3f003a06,0x3f5d924d,
0x3f13682a,0x3f514d3d,0x3f0af1b7,0x3f570348,0x3f0242b1,0x3f5c61c7,0x3ef2bd43,0x3f61668a,0x3ee0924f,0x3f660f88,0x3ece0bea,0x3f6a5ad9,0x3ebb31a0,0x3f6e46be,0x3ea80b1f,0x3f71d19f,
0x3ee63375,0x3f64aa59,0x3ed0eb2a,0x3f69b7e4,0x3ebb31a0,0x3f6e46be,0x3ea5129f,0x3f725470,0x3e8e9a22,0x3f75dec6,0x3e6fa8b2,0x3f78e3d6,0x3e419b37,0x3f7b61fc,0x3e1324ca,0x3f7d57de,
0x3ec3ef15,0x3f6c835e,0x3eac7cd4,0x3f710908,0x3e94a031,0x3f74fa0b,0x3e78cfcc,0x3f7853f8,0x3e47c5c2,0x3f7b14be,0x3e164083,0x3f7d3aac,0x3dc8bd36,0x3f7ec46d,0x3d48fb30,0x3f7fb10f,
0x3e78cfcc,0x3f7853f8,0x3e419b37,0x3f7b61fc,0x3e09cf86,0x3f7dabcc,0x3da3308c,0x3f7f2f9d,0x3cc90ab0,0x3f7fec43,0xbcfb49ba,0x3f7fe129,0xbdafb680,0x3f7f0e58,0xbe1008b7,0x3f7d7474,
0x3dc8bd36,0x3f7ec46d,0x3d16c32c,0x3f7fd397,0xbcc90ab0,0x3f7fec43,0xbdafb680,0x3f7f0e58,0xbe164083,0x3f7d3aac,0xbe541501,0x3f7a7302,0xbe888e93,0x3f76ba07,0xbea68f12,0x3f721352,
0xbd48fb30,0x3f7fb10f,0xbdee3876,0x3f7e4323,0xbe3b6ecf,0x3f7baccd,0xbe7ee6e1,0x3f77f110,0xbea09ae5,0x3f731447,0xbec1071e,0x3f6d1c1d,0xbee0924f,0x3f660f88,0xbeff17b2,0x3f5df6be,
0x3ea09ae5,0x3f731447,0x3e870ada,0x3f76ef5b,0x3e5a3997,0x3f7a1e84,0x3e25c58c,0x3f7c9f8a,0x3de1bc2e,0x3f7e70b0,0x3d6ea038,0x3f7f90b1,0x3bc90f88,0x3f7ffec4,0xbd3c6dd5,0x3f7fba9e,
0x3e2f10a2,0x3f7c3b28,0x3de7fa9a,0x3f7e5a38,0x3d621469,0x3f7f9c18,0xbb490fc6,0x3f7fffb1,0xbd7b2b74,0x3f7f84ab,0xbdf475c0,0x3f7e2b72,0xbe354098,0x3f7bf531,0xbe6fa8b2,0x3f78e3d6,
0x3cc90ab0,0x3f7fec43,0xbd2351cb,0x3f7fcbe2,0xbdd53db9,0x3f7e9bc9,0xbe2bf804,0x3f7c5d3a,0xbe6c9a7f,0x3f791298,0xbe9620d2,0x3f74bf62,0xbeb554ec,0x3f6f6830,0xbed3c867,0x3f6912ae,
0xbdfab273,0x3f7e1324,0xbe44b0b9,0x3f7b3bab,0xbe8586ce,0x3f772417,0xbea80b1f,0x3f71d19f,0xbec9b953,0x3f6b4b0c,0xbeea6681,0x3f6398ac,0xbf04f484,0x3f5ac450,0xbf140c5f,0x3f50d937,
0xbe47c5c2,0x3f7b14be,0xbe888e93,0x3f76ba07,0xbeac7cd4,0x3f710908,0xbecf7bca,0x3f6a09a7,0xbef15aea,0x3f61c598,0xbf08f59b,0x3f584853,0xbf187fc0,0x3f4d9f02,0xbf273656,0x3f41d870,
0xbeac7cd4,0x3f710908,0xbed25a09,0x3f696591,0xbef6e0cb,0x3f604621,0xbf0cead0,0x3f55b993,0xbf1d7fd1,0x3f49d112,0xbf2d1469,0x3f3ca003,0xbf3b8f3b,0x3f2e3bde,0xbf48d8b3,0x3f1ebc12,
0xbef15aea,0x3f61c598,0xbf0b9a6b,0x3f5695e5,0xbf1d7fd1,0x3f49d112,0xbf2e3bde,0x3f3b8f3b,0xbf3daef9,0x3f2beb4a,0xbf4bbbf8,0x3f1b02c6,0xbf584853,0x3f08f59b,0xbf633c5a,0x3eebcbbb,
0xbf187fc0,0x3f4d9f02,0xbf2ac082,0x3f3ebc1b,0xbf3b8f3b,0x3f2e3bde,0xbf4ac77f,0x3f1c420c,0xbf584853,0x3f08f59b,0xbf63f473,0x3ee900b7,0xbf6db293,0x3ebe1d4a,0xbf756d97,0x3e919ddd,
0xbe888e93,0x3f76ba07,0xbeadf73c,0x3f70c501,0xbed25a09,0x3f696591,0xbef58035,0x3f60a6cf,0xbf0b9a6b,0x3f5695e5,0xbf1ba299,0x3f4b41fa,0xbf2ac082,0x3f3ebc1b,0xbf38dd65,0x3f311722,
0xbecf7bca,0x3f6a09a7,0xbef58035,0x3f60a6cf,0xbf0cead0,0x3f55b993,0xbf1e1e22,0x3f495521,0xbf2e3bde,0x3f3b8f3b,0xbf3d27b8,0x3f2c800f,0xbf4ac77f,0x3f1c420c,0xbf570348,0x3f0af1b7,
0xbf08f59b,0x3f584853,0xbf1ba299,0x3f4b41fa,0xbf2d1469,0x3f3ca003,0xbf3d27b8,0x3f2c800f,0xbf4bbbf8,0x3f1b02c6,0xbf58b3a1,0x3f084b92,0xbf63f473,0x3ee900b7,0xbf6d67a1,0x3ebf926f,
0xbf273656,0x3f41d870,0xbf38dd65,0x3f311722,0xbf48d8b3,0x3f1ebc12,0xbf570348,0x3f0af1b7,0xbf633c5a,0x3eebcbbb,0xbf6d67a1,0x3ebf926f,0xbf756d97,0x3e919ddd,0xbf7b3bab,0x3e44b0b9,
0xbf3504f3,0x3f3504f3,0xbf45e403,0x3f226799,0xbf54db31,0x3f0e39da,0xbf61c598,0x3ef15aea,0xbf6c835e,0x3ec3ef15,0xbf74fa0b,0x3e94a031,0xbf7b14be,0x3e47c5c2,0xbf7ec46d,0x3dc8bd36,
0xbf4d9f02,0x3f187fc0,0xbf5c61c7,0x3f0242b1,0xbf68bf3c,0x3ed53641,0xbf7294f8,0x3ea395c5,0xbf79c79d,0x3e605c13,0xbf7e4323,0x3dee3876,0xbf7ffb11,0x3c490e90,0xbf7eea9d,0xbdbc3ac3,
0xbf61c598,0x3ef15aea,0xbf6db293,0x3ebe1d4a,0xbf76ba07,0x3e888e93,0xbf7cbfc9,0x3e22abb6,0xbf7fb10f,0x3d48fb30,0xbf7f84ab,0xbd7b2b74,0xbf7c3b28,0xbe2f10a2,0xbf75dec6,0xbe8e9a22,
0xbf710908,0x3eac7cd4,0xbf796e4e,0x3e667c66,0xbf7e70b0,0x3de1bc2e,0xbf7ffec4,0xbbc90f88,0xbf7e1324,0xbdfab273,0xbf78b47b,0xbe72b651,0xbf6ff573,0xbeb263ef,0xbf63f473,0xbee900b7,
0xbf41d870,0x3f273656,0xbf51c0c2,0x3f12c39a,0xbf5f8327,0x3ef9a02d,0xbf6afb8c,0x3ecb2aae,0xbf740bdd,0x3e9aa086,0xbf7a9c59,0x3e5101f1,0xbf7e9bc9,0x3dd53db9,0xbf7fffb1,0x3b490fc6,
0xbf584853,0x3f08f59b,0xbf65b710,0x3ee1fb6a,0xbf708066,0x3eaf713a,0xbf788486,0x3e75c35a,0xbf7dabcc,0x3e09cf86,0xbf7fe705,0x3ce22a7a,0xbf7f2f9d,0xbda3308c,0xbf7b87b2,0xbe3e853e,
0xbf6a09a7,0x3ecf7bca,0xbf74484b,0x3e9920fe,0xbf7b61fc,0x3e419b37,0xbf7f3f54,0x3d9cecf9,0xbf7fd397,0xbd16c32c,0xbf7d1cdd,0xbe195be0,0xbf772417,0xbe8586ce,0xbf6dfcf2,0xbebca7af,
0xbf76ba07,0x3e888e93,0xbf7d1cdd,0x3e195be0,0xbf7fe129,0x3cfb49ba,0xbf7efcc9,0xbdb5f8da,0xbf7a7302,0xbe541501,0xbf725470,0xbea5129f,0xbf66becc,0xbeddbe79,0xbf57dc7f,0xbf099f4e,
0xbf7b14be,0x3e47c5c2,0xbf7f4e6d,0x3d96a905,0xbf7fb10f,0xbd48fb30,0xbf7c3b28,0xbe2f10a2,0xbf74fa0b,0xbe94a031,0xbf6a09a7,0xbecf7bca,0xbf5b941a,0xbf039c3d,0xbf49d112,0xbf1d7fd1,
0xbf7fb10f,0x3d48fb30,0xbf7f2f9d,0xbda3308c,0xbf7a7302,0xbe541501,0xbf718f57,0xbea986c4,0xbf64aa59,0xbee63375,0xbf53fac3,0xbf0f8784,0xbf3fc767,0xbf299415,0xbf286605,0xbf40d0da,
0xbf7ec46d,0xbdc8bd36,0xbf791298,0xbe6c9a7f,0xbf6ed89e,0xbeb8442a,0xbf604621,0xbef6e0cb,0xbf4d9f02,0xbf187fc0,0xbf373a23,0xbf32c8c9,0xbf1d7fd1,0xbf49d112,0xbf00e7e4,0xbf5d2d53,
0xbf7853f8,0xbe78cfcc,0xbf6d1c1d,0xbec1071e,0xbf5d2d53,0xbf00e7e4,0xbf48d8b3,0xbf1ebc12,0xbf3085bb,0xbf396842,0xbf14b039,0xbf5064af,0xbeebcbbb,0xbf633c5a,0xbea986c4,0xbf718f57,
0xbf7e1324,0x3dfab273,0xbf7fffb1,0xbb490fc6,0xbf7de0b1,0xbe039502,0xbf77beb7,0xbe80f8c0,0xbf6db293,0xbebe1d4a,0xbf5fe4e9,0xbef840c8,0xbf4e8d90,0xbf173c07,0xbf39f2ac,0xbf2ff3e6,
0xbf7fec43,0xbcc90ab0,0xbf7cdf6c,0xbe1f917b,0xbf756d97,0xbe919ddd,0xbf69b7e4,0xbed0eb2a,0xbf59f26a,0xbf064b82,0xbf466354,0xbf21cbfb,0xbf2f61a5,0xbf3a7ca4,0xbf1553b7,0xbf4fefa8,
0xbf7c3b28,0xbe2f10a2,0xbf73ced9,0xbe9c1faf,0xbf66becc,0xbeddbe79,0xbf554aa4,0xbf0d9281,0xbf3fc767,0xbf299415,0xbf269de3,0xbf425b89,0xbf0a48ad,0xbf577026,0xbed6a399,0xbf686b39,
0xbf731447,0xbea09ae5,0xbf650479,0xbee4cbfe,0xbf5233c6,0xbf121eb0,0xbf3b0629,0xbf2ecef7,0xbf1ff6cb,0xbf47de65,0xbf019573,0xbf5cc7d1,0xbec1071e,0xbf6d1c1d,0xbe75c35a,0xbf788486,
0xbf6c835e,0xbec3ef15,0xbf5b941a,0xbf039c3d,0xbf45e403,0xbf226799,0xbf2beb4a,0xbf3daef9,0xbf0e39da,0xbf54db31,0xbedae880,0xbf676bd8,0xbe94a031,0xbf74fa0b,0xbe164083,0xbf7d3aac,
0xbf5b941a,0xbf039c3d,0xbf44e3f5,0xbf239da9,0xbf299415,0xbf3fc767,0xbf0a48ad,0xbf577026,0xbecf7bca,0xbf6a09a7,0xbe8586ce,0xbf772417,0xbde1bc2e,0xbf7e70b0,0x3d2fe007,0xbf7fc38f,
0xbf45e403,0xbf226799,0xbf299415,0xbf3fc767,0xbf08f59b,0xbf584853,0xbec9b953,0xbf6b4b0c,0xbe78cfcc,0xbf7853f8,0xbdafb680,0xbf7f0e58,0x3d96a905,0xbf7f4e6d,0x3e6c9a7f,0xbf791298,
0xbf2beb4a,0xbf3daef9,0xbf0a48ad,0xbf577026,0xbec9b953,0xbf6b4b0c,0xbe72b651,0xbf78b47b,0xbd96a905,0xbf7f4e6d,0x3dbc3ac3,0xbf7eea9d,0x3e827dc0,0xbf778bc5,0x3ed25a09,0xbf696591,
0xbf64aa59,0xbee63375,0xbf50d937,0xbf140c5f,0xbf385216,0xbf31a81d,0xbf1ba299,0xbf4b41fa,0xbef6e0cb,0xbf604621,0xbeb0eacb,0xbf703b37,0xbe4dee60,0xbf7ac516,0xbd55880e,0xbf7fa6e3,
0xbf514d3d,0xbf13682a,0xbf37c655,0xbf3238aa,0xbf19c200,0xbf4cae79,0xbeeff7fb,0xbf62241a,0xbea68f12,0xbf721352,0xbe3228d4,0xbf7c187a,0xbc96c9b6,0xbf7ff4e6,0x3e0cec4a,0xbf7d906e,
0xbf396842,0xbf3085bb,0xbf1a6293,0xbf4c3578,0xbeee9479,0xbf628210,0xbea21887,0xbf72d4eb,0xbe22abb6,0xbf7cbfc9,0x3b490fc6,0xbf7fffb1,0x3e28defc,0xbf7c7eb0,0x3ea5129f,0xbf725470,
0xbf1d7fd1,0xbf49d112,0xbef2bd43,0xbf61668a,0xbea395c5,0xbf7294f8,0xbe1f917b,0xbf7cdf6c,0x3c490e90,0xbf7ffb11,0x3e3857ec,0xbf7bd14d,0x3eaf713a,0xbf708066,0x3efdbabb,0xbf5e5aa6,
0xbf0e39da,0xbf54db31,0xbecf7bca,0xbf6a09a7,0xbe78cfcc,0xbf7853f8,0xbd96a905,0xbf7f4e6d,0x3dc8bd36,0xbf7ec46d,0x3e888e93,0xbf76ba07,0x3edae880,0xbf676bd8,0x3f13682a,0xbf514d3d,
0xbedae880,0xbf676bd8,0xbe8586ce,0xbf772417,0xbdafb680,0xbf7f0e58,0x3dbc3ac3,0xbf7eea9d,0x3e888e93,0xbf76ba07,0x3eddbe79,0xbf66becc,0x3f15f6d9,0xbf4f7a1f,0x3f385216,0xbf31a81d,
0xbe94a031,0xbf74fa0b,0xbde1bc2e,0xbf7e70b0,0x3d96a905,0xbf7f4e6d,0x3e827dc0,0xbf778bc5,0x3edae880,0xbf676bd8,0x3f15f6d9,0xbf4f7a1f,0x3f396842,0xbf3085bb,0x3f5695e5,0xbf0b9a6b,
0xbe164083,0xbf7d3aac,0x3d2fe007,0xbf7fc38f,0x3e6c9a7f,0xbf791298,0x3ed25a09,0xbf696591,0x3f13682a,0xbf514d3d,0x3f385216,0xbf31a81d,0x3f5695e5,0xbf0b9a6b,0x3f6d1c1d,0xbec1071e,
0xbefc5d27,0xbf5ebe05,0xbeab0201,0xbf714c7a,0xbe28defc,0xbf7c7eb0,0x3c16cb58,0xbf7ffd39,0x3e3b6ecf,0xbf7baccd,0x3eb3dca5,0xbf6faf1b,0x3f0242b1,0xbf5c61c7,0x3f269de3,0xbf425b89,
0xbeb8442a,0xbf6ed89e,0xbe3e853e,0xbf7b87b2,0xbbc90f88,0xbf7ffec4,0x3e3228d4,0xbf7c187a,0x3eb263ef,0xbf6ff573,0x3f02ef9f,0xbf5bfb34,0x3f286605,0xbf40d0da,0x3f485bca,0xbf1f599f,
0xbe605c13,0xbf79c79d,0xbd0a342f,0xbf7fdaaf,0x3e1c76de,0xbf7cfe73,0x3eab0201,0xbf714c7a,0x3f00e7e4,0xbf5d2d53,0x3f27ce61,0xbf4154e1,0x3f48d8b3,0xbf1ebc12,0x3f62df7b,0xbeed3063,
0xbd96a905,0xbf7f4e6d,0x3df475c0,0xbf7e2b72,0x3e9d9e78,0xbf73913f,0x3ef840c8,0xbf5fe4e9,0x3f24d225,0xbf43e200,0x3f476085,0xbf209393,0x3f628210,0xbeee9479,0x3f75341d,0xbe931f35,
0x3e003e00,0,0x3e003e00,0,0x3e003e00,0,0x3e003e00,0,0x3e003e00,0,0x3e003e00,0,0x3e003e00,0,0x3e003e00,0,
0x3dfb3e00,0x3cc80000,0xbcc80000,0x3dfb3e00,0x3dd53ded,0x3d8e3d44,0xbd8ebd44,0x3dd53ded,0x3d8e3db5,0x3dd53db5,0xbdd5bdb5,0x3d8e3db5,0x3cc83d44,0x3dfb3ded,0xbdfbbded,0x3cc83d44,
0x3ded3e00,0x3d440000,0xbdedbe00,0xbd440000,0x3d443db5,0x3ded3db5,0xbd44bdb5,0xbdedbdb5,0xbd440000,0x3ded3e00,0x3d440000,0xbdedbe00,0xbdedbdb5,0x3d443db5,0x3ded3db5,0xbd44bdb5,
0x3dd53e00,0x3d8e0000,0x3d8e0000,0xbdd5be00,0xbcc83d44,0x3dfb3ded,0x3dfb3ded,0x3cc8bd44,0xbdfbbdb5,0x3cc83db5,0x3cc83db5,0x3dfb3db5,0xbd8ebded,0xbdd5bd44,0xbdd5bd44,0x3d8e3ded,
0x3db53e00,0x3db50000,0x3db53e00,0x3db50000,0xbdb50000,0x3db53e00,0xbdb50000,0x3db53e00,0xbdb5be00,0xbdb50000,0xbdb5be00,0xbdb50000,0x3db50000,0xbdb5be00,0x3db50000,0xbdb5be00,
0x3d8e3e00,0x3dd50000,0xbdd50000,0x3d8e3e00,0xbdfbbd44,0x3cc83ded,0xbcc8bded,0xbdfbbd44,0x3cc8bdb5,0xbdfbbdb5,0x3dfb3db5,0x3cc8bdb5,0x3dd53ded,0x3d8ebd44,0xbd8e3d44,0x3dd53ded,
0x3d443e00,0x3ded0000,0xbd44be00,0xbded0000,0xbdedbdb5,0xbd443db5,0x3ded3db5,0x3d44bdb5,0x3ded0000,0xbd44be00,0xbded0000,0x3d443e00,0xbd443db5,0x3ded3db5,0x3d44bdb5,0xbdedbdb5,
0x3cc83e00,0x3dfb0000,0x3dfb0000,0xbcc8be00,0xbd8ebded,0xbdd53d44,0xbdd53d44,0x3d8e3ded,0x3dd53db5,0x3d8ebdb5,0x3d8ebdb5,0xbdd5bdb5,0xbdfbbd44,0xbcc83ded,0xbcc83ded,0x3dfb3d44,
0x3e00,0x3e000000,0x3e00,0x3e000000,0xbe00,0xbe000000,0xbe00,0xbe000000,0x3e00,0x3e000000,0x3e00,0x3e000000,0xbe00,0xbe000000,0xbe00,0xbe000000,
0xbcc83e00,0x3dfb0000,0xbdfb0000,0xbcc83e00,0x3d8ebded,0xbdd5bd44,0x3dd53d44,0x3d8ebded,0xbdd53db5,0x3d8e3db5,0xbd8ebdb5,0xbdd53db5,0x3dfbbd44,0xbcc8bded,0x3cc83ded,0x3dfbbd44,
0xbd443e00,0x3ded0000,0x3d44be00,0xbded0000,0x3dedbdb5,0xbd44bdb5,0xbded3db5,0x3d443db5,0xbded0000,0xbd443e00,0x3ded0000,0x3d44be00,0x3d443db5,0x3dedbdb5,0xbd44bdb5,0xbded3db5,
0xbd8e3e00,0x3dd50000,0x3dd50000,0x3d8ebe00,0x3dfbbd44,0x3cc8bded,0x3cc8bded,0xbdfb3d44,0xbcc8bdb5,0xbdfb3db5,0xbdfb3db5,0x3cc83db5,0xbdd53ded,0x3d8e3d44,0x3d8e3d44,0x3dd5bded,
0xbdb53e00,0x3db50000,0xbdb53e00,0x3db50000,0x3db50000,0x3db5be00,0x3db50000,0x3db5be00,0x3db5be00,0xbdb50000,0x3db5be00,0xbdb50000,0xbdb50000,0xbdb53e00,0xbdb50000,0xbdb53e00,
0xbdd53e00,0x3d8e0000,0xbd8e0000,0xbdd53e00,0x3cc83d44,0x3dfbbded,0xbdfb3ded,0x3cc83d44,0x3dfbbdb5,0x3cc8bdb5,0xbcc83db5,0x3dfbbdb5,0x3d8ebded,0xbdd53d44,0x3dd5bd44,0x3d8ebded,
0xbded3e00,0x3d440000,0x3dedbe00,0xbd440000,0xbd443db5,0x3dedbdb5,0x3d44bdb5,0xbded3db5,0x3d440000,0x3dedbe00,0xbd440000,0xbded3e00,0x3dedbdb5,0x3d44bdb5,0xbded3db5,0xbd443db5,
0xbdfb3e00,0x3cc80000,0x3cc80000,0x3dfbbe00,0xbdd53ded,0x3d8ebd44,0x3d8ebd44,0x3dd5bded,0xbd8e3db5,0x3dd5bdb5,0x3dd5bdb5,0x3d8ebdb5,0xbcc83d44,0x3dfbbded,0x3dfbbded,0x3cc8bd44,
0xbe003e00,0,0xbe003e00,0,0xbe003e00,0,0xbe003e00,0,0xbe003e00,0,0xbe003e00,0,0xbe003e00,0,0xbe003e00,0,
0xbdfb3e00,0xbcc80000,0x3cc80000,0xbdfb3e00,0xbdd53ded,0xbd8e3d44,0x3d8ebd44,0xbdd53ded,0xbd8e3db5,0xbdd53db5,0x3dd5bdb5,0xbd8e3db5,0xbcc83d44,0xbdfb3ded,0x3dfbbded,0xbcc83d44,
0xbded3e00,0xbd440000,0x3dedbe00,0x3d440000,0xbd443db5,0xbded3db5,0x3d44bdb5,0x3dedbdb5,0x3d440000,0xbded3e00,0xbd440000,0x3dedbe00,0x3dedbdb5,0xbd443db5,0xbded3db5,0x3d44bdb5,
0xbdd53e00,0xbd8e0000,0xbd8e0000,0x3dd5be00,0x3cc83d44,0xbdfb3ded,0xbdfb3ded,0xbcc8bd44,0x3dfbbdb5,0xbcc83db5,0xbcc83db5,0xbdfb3db5,0x3d8ebded,0x3dd5bd44,0x3dd5bd44,0xbd8e3ded,
0xbdb53e00,0xbdb50000,0xbdb53e00,0xbdb50000,0x3db50000,0xbdb53e00,0x3db50000,0xbdb53e00,0x3db5be00,0x3db50000,0x3db5be00,0x3db50000,0xbdb50000,0x3db5be00,0xbdb50000,0x3db5be00,
0xbd8e3e00,0xbdd50000,0x3dd50000,0xbd8e3e00,0x3dfbbd44,0xbcc83ded,0x3cc8bded,0x3dfbbd44,0xbcc8bdb5,0x3dfbbdb5,0xbdfb3db5,0xbcc8bdb5,0xbdd53ded,0xbd8ebd44,0x3d8e3d44,0xbdd53ded,
0xbd443e00,0xbded0000,0x3d44be00,0x3ded0000,0x3dedbdb5,0x3d443db5,0xbded3db5,0xbd44bdb5,0xbded0000,0x3d44be00,0x3ded0000,0xbd443e00,0x3d443db5,0xbded3db5,0xbd44bdb5,0x3dedbdb5,
0xbcc83e00,0xbdfb0000,0xbdfb0000,0x3cc8be00,0x3d8ebded,0x3dd53d44,0x3dd53d44,0xbd8e3ded,0xbdd53db5,0xbd8ebdb5,0xbd8ebdb5,0x3dd5bdb5,0x3dfbbd44,0x3cc83ded,0x3cc83ded,0xbdfb3d44,
0x3e00,0xbe000000,0x3e00,0xbe000000,0xbe00,0x3e000000,0xbe00,0x3e000000,0x3e00,0xbe000000,0x3e00,0xbe000000,0xbe00,0x3e000000,0xbe00,0x3e000000,
0x3cc83e00,0xbdfb0000,0x3dfb0000,0x3cc83e00,0xbd8ebded,0x3dd5bd44,0xbdd53d44,0xbd8ebded,0x3dd53db5,0xbd8e3db5,0x3d8ebdb5,0x3dd53db5,0xbdfbbd44,0x3cc8bded,0xbcc83ded,0xbdfbbd44,
0x3d443e00,0xbded0000,0xbd44be00,0x3ded0000,0xbdedbdb5,0x3d44bdb5,0x3ded3db5,0xbd443db5,0x3ded0000,0x3d443e00,0xbded0000,0xbd44be00,0xbd443db5,0xbdedbdb5,0x3d44bdb5,0x3ded3db5,
0x3d8e3e00,0xbdd50000,0xbdd50000,0xbd8ebe00,0xbdfbbd44,0xbcc8bded,0xbcc8bded,0x3dfb3d44,0x3cc8bdb5,0x3dfb3db5,0x3dfb3db5,0xbcc83db5,0x3dd53ded,0xbd8e3d44,0xbd8e3d44,0xbdd5bded,
0x3db53e00,0xbdb50000,0x3db53e00,0xbdb50000,0xbdb50000,0xbdb5be00,0xbdb50000,0xbdb5be00,0xbdb5be00,0x3db50000,0xbdb5be00,0x3db50000,0x3db50000,0x3db53e00,0x3db50000,0x3db53e00,
0x3dd53e00,0xbd8e0000,0x3d8e0000,0x3dd53e00,0xbcc83d44,0xbdfbbded,0x3dfb3ded,0xbcc83d44,0xbdfbbdb5,0xbcc8bdb5,0x3cc83db5,0xbdfbbdb5,0xbd8ebded,0x3dd53d44,0xbdd5bd44,0xbd8ebded,
0x3ded3e00,0xbd440000,0xbdedbe00,0x3d440000,0x3d443db5,0xbdedbdb5,0xbd44bdb5,0x3ded3db5,0xbd440000,0xbdedbe00,0x3d440000,0x3ded3e00,0xbdedbdb5,0xbd44bdb5,0x3ded3db5,0x3d443db5,
0x3dfb3e00,0xbcc80000,0xbcc80000,0xbdfbbe00,0x3dd53ded,0xbd8ebd44,0xbd8ebd44,0xbdd5bded,0x3d8e3db5,0xbdd5bdb5,0xbdd5bdb5,0xbd8ebdb5,0x3cc83d44,0xbdfbbded,0xbdfbbded,0xbcc8bd44,
0x3e003e00,0,0x3e003e00,0,0x3e003e00,0,0x3e003e00,0,0x3e003e00,0,0x3e003e00,0,0x3e003e00,0,0x3e003e00,0,
0xbdfbbe00,0xbcc80000,0x3cc80000,0xbdfbbe00,0xbdd5bded,0xbd8ebd44,0x3d8e3d44,0xbdd5bded,0xbd8ebdb5,0xbdd5bdb5,0x3dd53db5,0xbd8ebdb5,0xbcc8bd44,0xbdfbbded,0x3dfb3ded,0xbcc8bd44,
0x3ded3e00,0x3d440000,0xbdedbe00,0xbd440000,0x3d443db5,0x3ded3db5,0xbd44bdb5,0xbdedbdb5,0xbd440000,0x3ded3e00,0x3d440000,0xbdedbe00,0xbdedbdb5,0x3d443db5,0x3ded3db5,0xbd44bdb5,
0xbdd5be00,0xbd8e0000,0xbd8e0000,0x3dd53e00,0x3cc8bd44,0xbdfbbded,0xbdfbbded,0xbcc83d44,0x3dfb3db5,0xbcc8bdb5,0xbcc8bdb5,0xbdfbbdb5,0x3d8e3ded,0x3dd53d44,0x3dd53d44,0xbd8ebded,
0x3db53e00,0x3db50000,0x3db53e00,0x3db50000,0xbdb50000,0x3db53e00,0xbdb50000,0x3db53e00,0xbdb5be00,0xbdb50000,0xbdb5be00,0xbdb50000,0x3db50000,0xbdb5be00,0x3db50000,0xbdb5be00,
0xbd8ebe00,0xbdd50000,0x3dd50000,0xbd8ebe00,0x3dfb3d44,0xbcc8bded,0x3cc83ded,0x3dfb3d44,0xbcc83db5,0x3dfb3db5,0xbdfbbdb5,0xbcc83db5,0xbdd5bded,0xbd8e3d44,0x3d8ebd44,0xbdd5bded,
0x3d443e00,0x3ded0000,0xbd44be00,0xbded0000,0xbdedbdb5,0xbd443db5,0x3ded3db5,0x3d44bdb5,0x3ded0000,0xbd44be00,0xbded0000,0x3d443e00,0xbd443db5,0x3ded3db5,0x3d44bdb5,0xbdedbdb5,
0xbcc8be00,0xbdfb0000,0xbdfb0000,0x3cc83e00,0x3d8e3ded,0x3dd5bd44,0x3dd5bd44,0xbd8ebded,0xbdd5bdb5,0xbd8e3db5,0xbd8e3db5,0x3dd53db5,0x3dfb3d44,0x3cc8bded,0x3cc8bded,0xbdfbbd44,
0x3e00,0x3e000000,0x3e00,0x3e000000,0xbe00,0xbe000000,0xbe00,0xbe000000,0x3e00,0x3e000000,0x3e00,0x3e000000,0xbe00,0xbe000000,0xbe00,0xbe000000,
0x3cc8be00,0xbdfb0000,0x3dfb0000,0x3cc8be00,0xbd8e3ded,0x3dd53d44,0xbdd5bd44,0xbd8e3ded,0x3dd5bdb5,0xbd8ebdb5,0x3d8e3db5,0x3dd5bdb5,0xbdfb3d44,0x3cc83ded,0xbcc8bded,0xbdfb3d44,
0xbd443e00,0x3ded0000,0x3d44be00,0xbded0000,0x3dedbdb5,0xbd44bdb5,0xbded3db5,0x3d443db5,0xbded0000,0xbd443e00,0x3ded0000,0x3d44be00,0x3d443db5,0x3dedbdb5,0xbd44bdb5,0xbded3db5,
0x3d8ebe00,0xbdd50000,0xbdd50000,0xbd8e3e00,0xbdfb3d44,0xbcc83ded,0xbcc83ded,0x3dfbbd44,0x3cc83db5,0x3dfbbdb5,0x3dfbbdb5,0xbcc8bdb5,0x3dd5bded,0xbd8ebd44,0xbd8ebd44,0xbdd53ded,
0xbdb53e00,0x3db50000,0xbdb53e00,0x3db50000,0x3db50000,0x3db5be00,0x3db50000,0x3db5be00,0x3db5be00,0xbdb50000,0x3db5be00,0xbdb50000,0xbdb50000,0xbdb53e00,0xbdb50000,0xbdb53e00,
0x3dd5be00,0xbd8e0000,0x3d8e0000,0x3dd5be00,0xbcc8bd44,0xbdfb3ded,0x3dfbbded,0xbcc8bd44,0xbdfb3db5,0xbcc83db5,0x3cc8bdb5,0xbdfb3db5,0xbd8e3ded,0x3dd5bd44,0xbdd53d44,0xbd8e3ded,
0xbded3e00,0x3d440000,0x3dedbe00,0xbd440000,0xbd443db5,0x3dedbdb5,0x3d44bdb5,0xbded3db5,0x3d440000,0x3dedbe00,0xbd440000,0xbded3e00,0x3dedbdb5,0x3d44bdb5,0xbded3db5,0xbd443db5,
0x3dfbbe00,0xbcc80000,0xbcc80000,0xbdfb3e00,0x3dd5bded,0xbd8e3d44,0xbd8e3d44,0xbdd53ded,0x3d8ebdb5,0xbdd53db5,0xbdd53db5,0xbd8e3db5,0x3cc8bd44,0xbdfb3ded,0xbdfb3ded,0xbcc83d44,
0xbe003e00,0,0xbe003e00,0,0xbe003e00,0,0xbe003e00,0,0xbe003e00,0,0xbe003e00,0,0xbe003e00,0,0xbe003e00,0,
0x3dfbbe00,0x3cc80000,0xbcc80000,0x3dfbbe00,0x3dd5bded,0x3d8ebd44,0xbd8e3d44,0x3dd5bded,0x3d8ebdb5,0x3dd5bdb5,0xbdd53db5,0x3d8ebdb5,0x3cc8bd44,0x3dfbbded,0xbdfb3ded,0x3cc8bd44,
0xbded3e00,0xbd440000,0x3dedbe00,0x3d440000,0xbd443db5,0xbded3db5,0x3d44bdb5,0x3dedbdb5,0x3d440000,0xbded3e00,0xbd440000,0x3dedbe00,0x3dedbdb5,0xbd443db5,0xbded3db5,0x3d44bdb5,
0x3dd5be00,0x3d8e0000,0x3d8e0000,0xbdd53e00,0xbcc8bd44,0x3dfbbded,0x3dfbbded,0x3cc83d44,0xbdfb3db5,0x3cc8bdb5,0x3cc8bdb5,0x3dfbbdb5,0xbd8e3ded,0xbdd53d44,0xbdd53d44,0x3d8ebded,
0xbdb53e00,0xbdb50000,0xbdb53e00,0xbdb50000,0x3db50000,0xbdb53e00,0x3db50000,0xbdb53e00,0x3db5be00,0x3db50000,0x3db5be00,0x3db50000,0xbdb50000,0x3db5be00,0xbdb50000,0x3db5be00,
0x3d8ebe00,0x3dd50000,0xbdd50000,0x3d8ebe00,0xbdfb3d44,0x3cc8bded,0xbcc83ded,0xbdfb3d44,0x3cc83db5,0xbdfb3db5,0x3dfbbdb5,0x3cc83db5,0x3dd5bded,0x3d8e3d44,0xbd8ebd44,0x3dd5bded,
0xbd443e00,0xbded0000,0x3d44be00,0x3ded0000,0x3dedbdb5,0x3d443db5,0xbded3db5,0xbd44bdb5,0xbded0000,0x3d44be00,0x3ded0000,0xbd443e00,0x3d443db5,0xbded3db5,0xbd44bdb5,0x3dedbdb5,
0x3cc8be00,0x3dfb0000,0x3dfb0000,0xbcc83e00,0xbd8e3ded,0xbdd5bd44,0xbdd5bd44,0x3d8ebded,0x3dd5bdb5,0x3d8e3db5,0x3d8e3db5,0xbdd53db5,0xbdfb3d44,0xbcc8bded,0xbcc8bded,0x3dfbbd44,
0x3e00,0xbe000000,0x3e00,0xbe000000,0xbe00,0x3e000000,0xbe00,0x3e000000,0x3e00,0xbe000000,0x3e00,0xbe000000,0xbe00,0x3e000000,0xbe00,0x3e000000,
0xbcc8be00,0x3dfb0000,0xbdfb0000,0xbcc8be00,0x3d8e3ded,0xbdd53d44,0x3dd5bd44,0x3d8e3ded,0xbdd5bdb5,0x3d8ebdb5,0xbd8e3db5,0xbdd5bdb5,0x3dfb3d44,0xbcc83ded,0x3cc8bded,0x3dfb3d44,
0x3d443e00,0xbded0000,0xbd44be00,0x3ded0000,0xbdedbdb5,0x3d44bdb5,0x3ded3db5,0xbd443db5,0x3ded0000,0x3d443e00,0xbded0000,0xbd44be00,0xbd443db5,0xbdedbdb5,0x3d44bdb5,0x3ded3db5,
0xbd8ebe00,0x3dd50000,0x3dd50000,0x3d8e3e00,0x3dfb3d44,0x3cc83ded,0x3cc83ded,0xbdfbbd44,0xbcc83db5,0xbdfbbdb5,0xbdfbbdb5,0x3cc8bdb5,0xbdd5bded,0x3d8ebd44,0x3d8ebd44,0x3dd53ded,
0x3db53e00,0xbdb50000,0x3db53e00,0xbdb50000,0xbdb50000,0xbdb5be00,0xbdb50000,0xbdb5be00,0xbdb5be00,0x3db50000,0xbdb5be00,0x3db50000,0x3db50000,0x3db53e00,0x3db50000,0x3db53e00,
0xbdd5be00,0x3d8e0000,0xbd8e0000,0xbdd5be00,0x3cc8bd44,0x3dfb3ded,0xbdfbbded,0x3cc8bd44,0x3dfb3db5,0x3cc83db5,0xbcc8bdb5,0x3dfb3db5,0x3d8e3ded,0xbdd5bd44,0x3dd53d44,0x3d8e3ded,
0x3ded3e00,0xbd440000,0xbdedbe00,0x3d440000,0x3d443db5,0xbdedbdb5,0xbd44bdb5,0x3ded3db5,0xbd440000,0xbdedbe00,0x3d440000,0x3ded3e00,0xbdedbdb5,0xbd44bdb5,0x3ded3db5,0x3d443db5,
0xbdfbbe00,0x3cc80000,0x3cc80000,0x3dfb3e00,0xbdd5bded,0x3d8e3d44,0x3d8e3d44,0x3dd53ded,0xbd8ebdb5,0x3dd53db5,0x3dd53db5,0x3d8e3db5,0xbcc8bd44,0x3dfb3ded,0x3dfb3ded,0x3cc83d44,
0x80008000,0x3e003e00,0x80008000,0x3e003e00,0x80008000,0x3e003e00,0x80008000,0x3e003e00,0x80008000,0x3e003e00,0x80008000,0x3e003e00,0x80008000,0x3e003e00,0x80008000,0x3e003e00,
0xbcc88000,0x3dfb3e00,0xbdfbbe00,0xbcc80000,0xbd8ebd44,0x3dd53ded,0xbdd5bded,0xbd8ebd44,0xbdd5bdb5,0x3d8e3db5,0xbd8ebdb5,0xbdd5bdb5,0xbdfbbded,0x3cc83d44,0xbcc8bd44,0xbdfbbded,
0xbd448000,0x3ded3e00,0x3d448000,0xbdedbe00,0xbdedbdb5,0x3d443db5,0x3ded3db5,0xbd44bdb5,0xbdedbe00,0xbd440000,0x3ded3e00,0x3d440000,0xbd44bdb5,0xbdedbdb5,0x3d443db5,0x3ded3db5,
0xbd8e8000,0x3dd53e00,0x3dd53e00,0x3d8e0000,0xbdfbbded,0xbcc83d44,0xbcc83d44,0x3dfb3ded,0xbcc8bdb5,0xbdfbbdb5,0xbdfbbdb5,0x3cc83db5,0x3dd53d44,0xbd8ebded,0xbd8ebded,0xbdd5bd44,
0xbdb58000,0x3db53e00,0xbdb58000,0x3db53e00,0xbdb5be00,0xbdb50000,0xbdb5be00,0xbdb50000,0x3db58000,0xbdb5be00,0x3db58000,0xbdb5be00,0x3db53e00,0x3db50000,0x3db53e00,0x3db50000,
0xbdd58000,0x3d8e3e00,0xbd8ebe00,0xbdd50000,0xbcc8bded,0xbdfbbd44,0x3dfb3d44,0xbcc8bded,0x3dfb3db5,0x3cc8bdb5,0xbcc83db5,0x3dfb3db5,0xbd8e3d44,0x3dd53ded,0xbdd5bded,0xbd8e3d44,
0xbded8000,0x3d443e00,0x3ded8000,0xbd44be00,0x3d44bdb5,0xbdedbdb5,0xbd443db5,0x3ded3db5,0x3d443e00,0x3ded0000,0xbd44be00,0xbded0000,0xbdedbdb5,0xbd443db5,0x3ded3db5,0x3d44bdb5,
0xbdfb8000,0x3cc83e00,0x3cc83e00,0x3dfb0000,0x3dd5bd44,0xbd8ebded,0xbd8ebded,0xbdd53d44,0xbd8e3db5,0x3dd53db5,0x3dd53db5,0x3d8ebdb5,0x3cc8bded,0xbdfbbd44,0xbdfbbd44,0xbcc83ded,
0xbe008000,0x3e00,0xbe008000,0x3e00,0x3e008000,0xbe00,0x3e008000,0xbe00,0xbe008000,0x3e00,0xbe008000,0x3e00,0x3e008000,0xbe00,0x3e008000,0xbe00,
0xbdfb8000,0xbcc83e00,0x3cc8be00,0xbdfb0000,0x3dd53d44,0x3d8ebded,0xbd8e3ded,0x3dd53d44,0xbd8ebdb5,0xbdd53db5,0x3dd5bdb5,0xbd8ebdb5,0x3cc83ded,0x3dfbbd44,0xbdfb3d44,0x3cc83ded,
0xbded8000,0xbd443e00,0x3ded8000,0x3d44be00,0x3d443db5,0x3dedbdb5,0xbd44bdb5,0xbded3db5,0x3d44be00,0xbded0000,0xbd443e00,0x3ded0000,0xbded3db5,0x3d443db5,0x3dedbdb5,0xbd44bdb5,
0xbdd58000,0xbd8e3e00,0xbd8e3e00,0x3dd50000,0xbcc83ded,0x3dfbbd44,0x3dfbbd44,0x3cc8bded,0x3dfbbdb5,0xbcc8bdb5,0xbcc8bdb5,0xbdfb3db5,0xbd8ebd44,0xbdd53ded,0xbdd53ded,0x3d8e3d44,
0xbdb58000,0xbdb53e00,0xbdb58000,0xbdb53e00,0xbdb53e00,0x3db50000,0xbdb53e00,0x3db50000,0x3db58000,0x3db5be00,0x3db58000,0x3db5be00,0x3db5be00,0xbdb50000,0x3db5be00,0xbdb50000,
0xbd8e8000,0xbdd53e00,0x3dd5be00,0xbd8e0000,0xbdfb3ded,0x3cc83d44,0xbcc8bd44,0xbdfb3ded,0xbcc83db5,0x3dfbbdb5,0xbdfb3db5,0xbcc83db5,0x3dd5bd44,0x3d8ebded,0xbd8e3ded,0x3dd5bd44,
0xbd448000,0xbded3e00,0x3d448000,0x3dedbe00,0xbded3db5,0xbd443db5,0x3dedbdb5,0x3d44bdb5,0xbded3e00,0x3d440000,0x3dedbe00,0xbd440000,0xbd443db5,0x3dedbdb5,0x3d44bdb5,0xbded3db5,
0xbcc88000,0xbdfb3e00,0xbdfb3e00,0x3cc80000,0xbd8e3d44,0xbdd53ded,0xbdd53ded,0x3d8ebd44,0xbdd53db5,0xbd8e3db5,0xbd8e3db5,0x3dd5bdb5,0xbdfb3ded,0xbcc83d44,0xbcc83d44,0x3dfbbded,
0x80008000,0xbe003e00,0x80008000,0xbe003e00,0x80008000,0xbe003e00,0x80008000,0xbe003e00,0x80008000,0xbe003e00,0x80008000,0xbe003e00,0x80008000,0xbe003e00,0x80008000,0xbe003e00,
0x3cc88000,0xbdfb3e00,0x3dfbbe00,0x3cc80000,0x3d8ebd44,0xbdd53ded,0x3dd5bded,0x3d8ebd44,0x3dd5bdb5,0xbd8e3db5,0x3d8ebdb5,0x3dd5bdb5,0x3dfbbded,0xbcc83d44,0x3cc8bd44,0x3dfbbded,
0x3d448000,0xbded3e00,0xbd448000,0x3dedbe00,0x3dedbdb5,0xbd443db5,0xbded3db5,0x3d44bdb5,0x3dedbe00,0x3d440000,0xbded3e00,0xbd440000,0x3d44bdb5,0x3dedbdb5,0xbd443db5,0xbded3db5,
0x3d8e8000,0xbdd53e00,0xbdd53e00,0xbd8e0000,0x3dfbbded,0x3cc83d44,0x3cc83d44,0xbdfb3ded,0x3cc8bdb5,0x3dfbbdb5,0x3dfbbdb5,0xbcc83db5,0xbdd53d44,0x3d8ebded,0x3d8ebded,0x3dd5bd44,
0x3db58000,0xbdb53e00,0x3db58000,0xbdb53e00,0x3db5be00,0x3db50000,0x3db5be00,0x3db50000,0xbdb58000,0x3db5be00,0xbdb58000,0x3db5be00,0xbdb53e00,0xbdb50000,0xbdb53e00,0xbdb50000,
0x3dd58000,0xbd8e3e00,0x3d8ebe00,0x3dd50000,0x3cc8bded,0x3dfbbd44,0xbdfb3d44,0x3cc8bded,0xbdfb3db5,0xbcc8bdb5,0x3cc83db5,0xbdfb3db5,0x3d8e3d44,0xbdd53ded,0x3dd5bded,0x3d8e3d44,
0x3ded8000,0xbd443e00,0xbded8000,0x3d44be00,0xbd44bdb5,0x3dedbdb5,0x3d443db5,0xbded3db5,0xbd443e00,0xbded0000,0x3d44be00,0x3ded0000,0x3dedbdb5,0x3d443db5,0xbded3db5,0xbd44bdb5,
0x3dfb8000,0xbcc83e00,0xbcc83e00,0xbdfb0000,0xbdd5bd44,0x3d8ebded,0x3d8ebded,0x3dd53d44,0x3d8e3db5,0xbdd53db5,0xbdd53db5,0xbd8ebdb5,0xbcc8bded,0x3dfbbd44,0x3dfbbd44,0x3cc83ded,
0x3e008000,0x3e00,0x3e008000,0x3e00,0xbe008000,0xbe00,0xbe008000,0xbe00,0x3e008000,0x3e00,0x3e008000,0x3e00,0xbe008000,0xbe00,0xbe008000,0xbe00,
0x3dfb8000,0x3cc83e00,0xbcc8be00,0x3dfb0000,0xbdd53d44,0xbd8ebded,0x3d8e3ded,0xbdd53d44,0x3d8ebdb5,0x3dd53db5,0xbdd5bdb5,0x3d8ebdb5,0xbcc83ded,0xbdfbbd44,0x3dfb3d44,0xbcc83ded,
0x3ded8000,0x3d443e00,0xbded8000,0xbd44be00,0xbd443db5,0xbdedbdb5,0x3d44bdb5,0x3ded3db5,0xbd44be00,0x3ded0000,0x3d443e00,0xbded0000,0x3ded3db5,0xbd443db5,0xbdedbdb5,0x3d44bdb5,
0x3dd58000,0x3d8e3e00,0x3d8e3e00,0xbdd50000,0x3cc83ded,0xbdfbbd44,0xbdfbbd44,0xbcc8bded,0xbdfbbdb5,0x3cc8bdb5,0x3cc8bdb5,0x3dfb3db5,0x3d8ebd44,0x3dd53ded,0x3dd53ded,0xbd8e3d44,
0x3db58000,0x3db53e00,0x3db58000,0x3db53e00,0x3db53e00,0xbdb50000,0x3db53e00,0xbdb50000,0xbdb58000,0xbdb5be00,0xbdb58000,0xbdb5be00,0xbdb5be00,0x3db50000,0xbdb5be00,0x3db50000,
0x3d8e8000,0x3dd53e00,0xbdd5be00,0x3d8e0000,0x3dfb3ded,0xbcc83d44,0x3cc8bd44,0x3dfb3ded,0x3cc83db5,0xbdfbbdb5,0x3dfb3db5,0x3cc83db5,0xbdd5bd44,0xbd8ebded,0x3d8e3ded,0xbdd5bd44,
0x3d448000,0x3ded3e00,0xbd448000,0xbdedbe00,0x3ded3db5,0x3d443db5,0xbdedbdb5,0xbd44bdb5,0x3ded3e00,0xbd440000,0xbdedbe00,0x3d440000,0x3d443db5,0xbdedbdb5,0xbd44bdb5,0x3ded3db5,
0x3cc88000,0x3dfb3e00,0x3dfb3e00,0xbcc80000,0x3d8e3d44,0x3dd53ded,0x3dd53ded,0xbd8ebd44,0x3dd53db5,0x3d8e3db5,0x3d8e3db5,0xbdd5bdb5,0x3dfb3ded,0x3cc83d44,0x3cc83d44,0xbdfbbded,
0x80008000,0x3e003e00,0x80008000,0x3e003e00,0x80008000,0x3e003e00,0x80008000,0x3e003e00,0x80008000,0x3e003e00,0x80008000,0x3e003e00,0x80008000,0x3e003e00,0x80008000,0x3e003e00,
0x3cc88000,0xbdfbbe00,0x3dfb3e00,0x3cc80000,0x3d8e3d44,0xbdd5bded,0x3dd53ded,0x3d8e3d44,0x3dd53db5,0xbd8ebdb5,0x3d8e3db5,0x3dd53db5,0x3dfb3ded,0xbcc8bd44,0x3cc83d44,0x3dfb3ded,
0xbd448000,0x3ded3e00,0x3d448000,0xbdedbe00,0xbdedbdb5,0x3d443db5,0x3ded3db5,0xbd44bdb5,0xbdedbe00,0xbd440000,0x3ded3e00,0x3d440000,0xbd44bdb5,0xbdedbdb5,0x3d443db5,0x3ded3db5,
0x3d8e8000,0xbdd5be00,0xbdd5be00,0xbd8e0000,0x3dfb3ded,0x3cc8bd44,0x3cc8bd44,0xbdfbbded,0x3cc83db5,0x3dfb3db5,0x3dfb3db5,0xbcc8bdb5,0xbdd5bd44,0x3d8e3ded,0x3d8e3ded,0x3dd53d44,
0xbdb58000,0x3db53e00,0xbdb58000,0x3db53e00,0xbdb5be00,0xbdb50000,0xbdb5be00,0xbdb50000,0x3db58000,0xbdb5be00,0x3db58000,0xbdb5be00,0x3db53e00,0x3db50000,0x3db53e00,0x3db50000,
0x3dd58000,0xbd8ebe00,0x3d8e3e00,0x3dd50000,0x3cc83ded,0x3dfb3d44,0xbdfbbd44,0x3cc83ded,0xbdfbbdb5,0xbcc83db5,0x3cc8bdb5,0xbdfbbdb5,0x3d8ebd44,0xbdd5bded,0x3dd53ded,0x3d8ebd44,
0xbded8000,0x3d443e00,0x3ded8000,0xbd44be00,0x3d44bdb5,0xbdedbdb5,0xbd443db5,0x3ded3db5,0x3d443e00,0x3ded0000,0xbd44be00,0xbded0000,0xbdedbdb5,0xbd443db5,0x3ded3db5,0x3d44bdb5,
0x3dfb8000,0xbcc8be00,0xbcc8be00,0xbdfb0000,0xbdd53d44,0x3d8e3ded,0x3d8e3ded,0x3dd5bd44,0x3d8ebdb5,0xbdd5bdb5,0xbdd5bdb5,0xbd8e3db5,0xbcc83ded,0x3dfb3d44,0x3dfb3d44,0x3cc8bded,
0xbe008000,0x3e00,0xbe008000,0x3e00,0x3e008000,0xbe00,0x3e008000,0xbe00,0xbe008000,0x3e00,0xbe008000,0x3e00,0x3e008000,0xbe00,0x3e008000,0xbe00,
0x3dfb8000,0x3cc8be00,0xbcc83e00,0x3dfb0000,0xbdd5bd44,0xbd8e3ded,0x3d8ebded,0xbdd5bd44,0x3d8e3db5,0x3dd5bdb5,0xbdd53db5,0x3d8e3db5,0xbcc8bded,0xbdfb3d44,0x3dfbbd44,0xbcc8bded,
0xbded8000,0xbd443e00,0x3ded8000,0x3d44be00,0x3d443db5,0x3dedbdb5,0xbd44bdb5,0xbded3db5,0x3d44be00,0xbded0000,0xbd443e00,0x3ded0000,0xbded3db5,0x3d443db5,0x3dedbdb5,0xbd44bdb5,
0x3dd58000,0x3d8ebe00,0x3d8ebe00,0xbdd50000,0x3cc8bded,0xbdfb3d44,0xbdfb3d44,0xbcc83ded,0xbdfb3db5,0x3cc83db5,0x3cc83db5,0x3dfbbdb5,0x3d8e3d44,0x3dd5bded,0x3dd5bded,0xbd8ebd44,
0xbdb58000,0xbdb53e00,0xbdb58000,0xbdb53e00,0xbdb53e00,0x3db50000,0xbdb53e00,0x3db50000,0x3db58000,0x3db5be00,0x3db58000,0x3db5be00,0x3db5be00,0xbdb50000,0x3db5be00,0xbdb50000,
0x3d8e8000,0x3dd5be00,0xbdd53e00,0x3d8e0000,0x3dfbbded,0xbcc8bd44,0x3cc83d44,0x3dfbbded,0x3cc8bdb5,0xbdfb3db5,0x3dfbbdb5,0x3cc8bdb5,0xbdd53d44,0xbd8e3ded,0x3d8ebded,0xbdd53d44,
0xbd448000,0xbded3e00,0x3d448000,0x3dedbe00,0xbded3db5,0xbd443db5,0x3dedbdb5,0x3d44bdb5,0xbded3e00,0x3d440000,0x3dedbe00,0xbd440000,0xbd443db5,0x3dedbdb5,0x3d44bdb5,0xbded3db5,
0x3cc88000,0x3dfbbe00,0x3dfbbe00,0xbcc80000,0x3d8ebd44,0x3dd5bded,0x3dd5bded,0xbd8e3d44,0x3dd5bdb5,0x3d8ebdb5,0x3d8ebdb5,0xbdd53db5,0x3dfbbded,0x3cc8bd44,0x3cc8bd44,0xbdfb3ded,
0x80008000,0xbe003e00,0x80008000,0xbe003e00,0x80008000,0xbe003e00,0x80008000,0xbe003e00,0x80008000,0xbe003e00,0x80008000,0xbe003e00,0x80008000,0xbe003e00,0x80008000,0xbe003e00,
0xbcc88000,0x3dfbbe00,0xbdfb3e00,0xbcc80000,0xbd8e3d44,0x3dd5bded,0xbdd53ded,0xbd8e3d44,0xbdd53db5,0x3d8ebdb5,0xbd8e3db5,0xbdd53db5,0xbdfb3ded,0x3cc8bd44,0xbcc83d44,0xbdfb3ded,
0x3d448000,0xbded3e00,0xbd448000,0x3dedbe00,0x3dedbdb5,0xbd443db5,0xbded3db5,0x3d44bdb5,0x3dedbe00,0x3d440000,0xbded3e00,0xbd440000,0x3d44bdb5,0x3dedbdb5,0xbd443db5,0xbded3db5,
0xbd8e8000,0x3dd5be00,0x3dd5be00,0x3d8e0000,0xbdfb3ded,0xbcc8bd44,0xbcc8bd44,0x3dfbbded,0xbcc83db5,0xbdfb3db5,0xbdfb3db5,0x3cc8bdb5,0x3dd5bd44,0xbd8e3ded,0xbd8e3ded,0xbdd53d44,
0x3db58000,0xbdb53e00,0x3db58000,0xbdb53e00,0x3db5be00,0x3db50000,0x3db5be00,0x3db50000,0xbdb58000,0x3db5be00,0xbdb58000,0x3db5be00,0xbdb53e00,0xbdb50000,0xbdb53e00,0xbdb50000,
0xbdd58000,0x3d8ebe00,0xbd8e3e00,0xbdd50000,0xbcc83ded,0xbdfb3d44,0x3dfbbd44,0xbcc83ded,0x3dfbbdb5,0x3cc83db5,0xbcc8bdb5,0x3dfbbdb5,0xbd8ebd44,0x3dd5bded,0xbdd53ded,0xbd8ebd44,
0x3ded8000,0xbd443e00,0xbded8000,0x3d44be00,0xbd44bdb5,0x3dedbdb5,0x3d443db5,0xbded3db5,0xbd443e00,0xbded0000,0x3d44be00,0x3ded0000,0x3dedbdb5,0x3d443db5,0xbded3db5,0xbd44bdb5,
0xbdfb8000,0x3cc8be00,0x3cc8be00,0x3dfb0000,0x3dd53d44,0xbd8e3ded,0xbd8e3ded,0xbdd5bd44,0xbd8ebdb5,0x3dd5bdb5,0x3dd5bdb5,0x3d8e3db5,0x3cc83ded,0xbdfb3d44,0xbdfb3d44,0xbcc8bded,
0x3e008000,0x3e00,0x3e008000,0x3e00,0xbe008000,0xbe00,0xbe008000,0xbe00,0x3e008000,0x3e00,0x3e008000,0x3e00,0xbe008000,0xbe00,0xbe008000,0xbe00,
0xbdfb8000,0xbcc8be00,0x3cc83e00,0xbdfb0000,0x3dd5bd44,0x3d8e3ded,0xbd8ebded,0x3dd5bd44,0xbd8e3db5,0xbdd5bdb5,0x3dd53db5,0xbd8e3db5,0x3cc8bded,0x3dfb3d44,0xbdfbbd44,0x3cc8bded,
0x3ded8000,0x3d443e00,0xbded8000,0xbd44be00,0xbd443db5,0xbdedbdb5,0x3d44bdb5,0x3ded3db5,0xbd44be00,0x3ded0000,0x3d443e00,0xbded0000,0x3ded3db5,0xbd443db5,0xbdedbdb5,0x3d44bdb5,
0xbdd58000,0xbd8ebe00,0xbd8ebe00,0x3dd50000,0xbcc8bded,0x3dfb3d44,0x3dfb3d44,0x3cc83ded,0x3dfb3db5,0xbcc83db5,0xbcc83db5,0xbdfbbdb5,0xbd8e3d44,0xbdd5bded,0xbdd5bded,0x3d8ebd44,
0x3db58000,0x3db53e00,0x3db58000,0x3db53e00,0x3db53e00,0xbdb50000,0x3db53e00,0xbdb50000,0xbdb58000,0xbdb5be00,0xbdb58000,0xbdb5be00,0xbdb5be00,0x3db50000,0xbdb5be00,0x3db50000,
0xbd8e8000,0xbdd5be00,0x3dd53e00,0xbd8e0000,0xbdfbbded,0x3cc8bd44,0xbcc83d44,0xbdfbbded,0xbcc8bdb5,0x3dfb3db5,0xbdfbbdb5,0xbcc8bdb5,0x3dd53d44,0x3d8e3ded,0xbd8ebded,0x3dd53d44,
0x3d448000,0x3ded3e00,0xbd448000,0xbdedbe00,0x3ded3db5,0x3d443db5,0xbdedbdb5,0xbd44bdb5,0x3ded3e00,0xbd440000,0xbdedbe00,0x3d440000,0x3d443db5,0xbdedbdb5,0xbd44bdb5,0x3ded3db5,
0xbcc88000,0xbdfbbe00,0xbdfbbe00,0x3cc80000,0xbd8ebd44,0xbdd5bded,0xbdd5bded,0x3d8e3d44,0xbdd5bdb5,0xbd8ebdb5,0xbd8ebdb5,0x3dd53db5,0xbdfbbded,0xbcc8bd44,0xbcc8bd44,0x3dfb3ded,
0x3e003e00,0,0x3e003e00,0,0x3e003e00,0,0x3e003e00,0,0x3e003e00,0,0x3e003e00,0,0x3e003e00,0,0x3e003e00,0,
0x3df53dff,0x3d153c49,0xbd15bc49,0x3df53dff,0x3dc63de2,0x3da23d71,0xbda2bd71,0x3dc63de2,0x3d713da2,0x3de23dc6,0xbde2bdc6,0x3d713da2,0x3c493d15,0x3dff3df5,0xbdffbdf5,0x3c493d15,
0x3dd53dfb,0x3d8e3cc8,0xbdd5bdfb,0xbd8ebcc8,0x3cc83d8e,0x3dfb3dd5,0xbcc8bd8e,0xbdfbbdd5,0xbd8ebcc8,0x3dd53dfb,0x3d8e3cc8,0xbdd5bdfb,0xbdfbbdd5,0x3cc83d8e,0x3dfb3dd5,0xbcc8bd8e,
0x3da23df5,0x3dc63d15,0x3dc63d15,0xbda2bdf5,0xbd713c49,0x3de23dff,0x3de23dff,0x3d71bc49,0xbdffbde2,0xbc493d71,0xbc493d71,0x3dff3de2,0xbd15bdc6,0xbdf5bda2,0xbdf5bda2,0x3d153dc6,
0x3d443ded,0x3ded3d44,0x3d443ded,0x3ded3d44,0xbdedbd44,0x3d443ded,0xbdedbd44,0x3d443ded,0xbd44bded,0xbdedbd44,0xbd44bded,0xbdedbd44,0x3ded3d44,0xbd44bded,0x3ded3d44,0xbd44bded,
0x3c493de2,0x3dff3d71,0xbdffbd71,0x3c493de2,0xbdf5bdc6,0xbd153da2,0x3d15bda2,0xbdf5bdc6,0x3da2bd15,0xbdc6bdf5,0x3dc63df5,0x3da2bd15,0x3d713dff,0x3de23c49,0xbde2bc49,0x3d713dff,
0xbcc83dd5,0x3dfb3d8e,0x3cc8bdd5,0xbdfbbd8e,0xbd8ebdfb,0xbdd53cc8,0x3d8e3dfb,0x3dd5bcc8,0x3dfb3d8e,0x3cc8bdd5,0xbdfbbd8e,0xbcc83dd5,0xbdd53cc8,0x3d8e3dfb,0x3dd5bcc8,0xbd8ebdfb,
0xbd713dc6,0x3de23da2,0x3de23da2,0x3d71bdc6,0x3c49bdf5,0xbdffbd15,0xbdffbd15,0xbc493df5,0x3d153dff,0x3df5bc49,0x3df5bc49,0xbd15bdff,0xbda2bde2,0xbdc63d71,0xbdc63d71,0x3da23de2,
0xbdb53db5,0x3db53db5,0xbdb53db5,0x3db53db5,0x3db5bdb5,0xbdb5bdb5,0x3db5bdb5,0xbdb5bdb5,0xbdb53db5,0x3db53db5,0xbdb53db5,0x3db53db5,0x3db5bdb5,0xbdb5bdb5,0x3db5bdb5,0xbdb5bdb5,
0xbde23da2,0x3d713dc6,0xbd71bdc6,0xbde23da2,0x3dffbd15,0xbc49bdf5,0x3c493df5,0x3dffbd15,0xbdf5bc49,0xbd153dff,0x3d15bdff,0xbdf5bc49,0x3dc63d71,0x3da2bde2,0xbda23de2,0x3dc63d71,
0xbdfb3d8e,0x3cc83dd5,0x3dfbbd8e,0xbcc8bdd5,0x3dd53cc8,0x3d8ebdfb,0xbdd5bcc8,0xbd8e3dfb,0xbcc8bdd5,0xbdfb3d8e,0x3cc83dd5,0x3dfbbd8e,0xbd8e3dfb,0x3dd53cc8,0x3d8ebdfb,0xbdd5bcc8,
0xbdff3d71,0xbc493de2,0xbc493de2,0x3dffbd71,0x3d153da2,0x3df5bdc6,0x3df5bdc6,0xbd15bda2,0x3dc6bdf5,0xbda2bd15,0xbda2bd15,0xbdc63df5,0xbde23c49,0xbd713dff,0xbd713dff,0x3de2bc49,
0xbded3d44,0xbd443ded,0xbded3d44,0xbd443ded,0xbd443ded,0x3dedbd44,0xbd443ded,0x3dedbd44,0x3dedbd44,0x3d44bded,0x3dedbd44,0x3d44bded,0x3d44bded,0xbded3d44,0x3d44bded,0xbded3d44,
0xbdc63d15,0xbda23df5,0x3da2bdf5,0xbdc63d15,0xbde23dff,0x3d713c49,0xbd71bc49,0xbde23dff,0x3c493d71,0x3dffbde2,0xbdff3de2,0x3c493d71,0x3df5bda2,0x3d15bdc6,0xbd153dc6,0x3df5bda2,
0xbd8e3cc8,0xbdd53dfb,0x3d8ebcc8,0x3dd5bdfb,0xbdfb3dd5,0xbcc83d8e,0x3dfbbdd5,0x3cc8bd8e,0xbdd53dfb,0x3d8ebcc8,0x3dd5bdfb,0xbd8e3cc8,0xbcc83d8e,0x3dfbbdd5,0x3cc8bd8e,0xbdfb3dd5,
0xbd153c49,0xbdf53dff,0xbdf53dff,0x3d15bc49,0xbda23d71,0xbdc63de2,0xbdc63de2,0x3da2bd71,0xbde23dc6,0xbd713da2,0xbd713da2,0x3de2bdc6,0xbdff3df5,0xbc493d15,0xbc493d15,0x3dffbdf5,
0,0xbe003e00,0,0xbe003e00,0,0xbe003e00,0,0xbe003e00,0,0xbe003e00,0,0xbe003e00,0,0xbe003e00,0,0xbe003e00,
0x3d15bc49,0xbdf53dff,0x3df5bdff,0x3d15bc49,0x3da2bd71,0xbdc63de2,0x3dc6bde2,0x3da2bd71,0x3de2bdc6,0xbd713da2,0x3d71bda2,0x3de2bdc6,0x3dffbdf5,0xbc493d15,0x3c49bd15,0x3dffbdf5,
0x3d8ebcc8,0xbdd53dfb,0xbd8e3cc8,0x3dd5bdfb,0x3dfbbdd5,0xbcc83d8e,0xbdfb3dd5,0x3cc8bd8e,0x3dd5bdfb,0x3d8ebcc8,0xbdd53dfb,0xbd8e3cc8,0x3cc8bd8e,0x3dfbbdd5,0xbcc83d8e,0xbdfb3dd5,
0x3dc6bd15,0xbda23df5,0xbda23df5,0xbdc63d15,0x3de2bdff,0x3d713c49,0x3d713c49,0xbde23dff,0xbc49bd71,0x3dffbde2,0x3dffbde2,0x3c493d71,0xbdf53da2,0x3d15bdc6,0x3d15bdc6,0x3df5bda2,
0x3dedbd44,0xbd443ded,0x3dedbd44,0xbd443ded,0x3d44bded,0x3dedbd44,0x3d44bded,0x3dedbd44,0xbded3d44,0x3d44bded,0xbded3d44,0x3d44bded,0xbd443ded,0xbded3d44,0xbd443ded,0xbded3d44,
0x3dffbd71,0xbc493de2,0x3c49bde2,0x3dffbd71,0xbd15bda2,0x3df5bdc6,0xbdf53dc6,0xbd15bda2,0xbdc63df5,0xbda2bd15,0x3da23d15,0xbdc63df5,0x3de2bc49,0xbd713dff,0x3d71bdff,0x3de2bc49,
0x3dfbbd8e,0x3cc83dd5,0xbdfb3d8e,0xbcc8bdd5,0xbdd5bcc8,0x3d8ebdfb,0x3dd53cc8,0xbd8e3dfb,0x3cc83dd5,0xbdfb3d8e,0xbcc8bdd5,0x3dfbbd8e,0x3d8ebdfb,0x3dd53cc8,0xbd8e3dfb,0xbdd5bcc8,
0x3de2bda2,0x3d713dc6,0x3d713dc6,0xbde23da2,0xbdff3d15,0xbc49bdf5,0xbc49bdf5,0x3dffbd15,0x3df53c49,0xbd153dff,0xbd153dff,0xbdf5bc49,0xbdc6bd71,0x3da2bde2,0x3da2bde2,0x3dc63d71,
0x3db5bdb5,0x3db53db5,0x3db5bdb5,0x3db53db5,0xbdb53db5,0xbdb5bdb5,0xbdb53db5,0xbdb5bdb5,0x3db5bdb5,0x3db53db5,0x3db5bdb5,0x3db53db5,0xbdb53db5,0xbdb5bdb5,0xbdb53db5,0xbdb5bdb5,
0x3d71bdc6,0x3de23da2,0xbde2bda2,0x3d71bdc6,0xbc493df5,0xbdffbd15,0x3dff3d15,0xbc493df5,0xbd15bdff,0x3df5bc49,0xbdf53c49,0xbd15bdff,0x3da23de2,0xbdc63d71,0x3dc6bd71,0x3da23de2,
0x3cc8bdd5,0x3dfb3d8e,0xbcc83dd5,0xbdfbbd8e,0x3d8e3dfb,0xbdd53cc8,0xbd8ebdfb,0x3dd5bcc8,0xbdfbbd8e,0x3cc8bdd5,0x3dfb3d8e,0xbcc83dd5,0x3dd5bcc8,0x3d8e3dfb,0xbdd53cc8,0xbd8ebdfb,
0xbc49bde2,0x3dff3d71,0x3dff3d71,0x3c493de2,0x3df53dc6,0xbd153da2,0xbd153da2,0xbdf5bdc6,0xbda23d15,0xbdc6bdf5,0xbdc6bdf5,0x3da2bd15,0xbd71bdff,0x3de23c49,0x3de23c49,0x3d713dff,
0xbd44bded,0x3ded3d44,0xbd44bded,0x3ded3d44,0x3ded3d44,0x3d443ded,0x3ded3d44,0x3d443ded,0x3d443ded,0xbdedbd44,0x3d443ded,0xbdedbd44,0xbdedbd44,0xbd44bded,0xbdedbd44,0xbd44bded,
0xbda2bdf5,0x3dc63d15,0xbdc6bd15,0xbda2bdf5,0x3d71bc49,0x3de23dff,0xbde2bdff,0x3d71bc49,0x3dff3de2,0xbc493d71,0x3c49bd71,0x3dff3de2,0x3d153dc6,0xbdf5bda2,0x3df53da2,0x3d153dc6,
0xbdd5bdfb,0x3d8e3cc8,0x3dd53dfb,0xbd8ebcc8,0xbcc8bd8e,0x3dfb3dd5,0x3cc83d8e,0xbdfbbdd5,0x3d8e3cc8,0x3dd53dfb,0xbd8ebcc8,0xbdd5bdfb,0x3dfb3dd5,0x3cc83d8e,0xbdfbbdd5,0xbcc8bd8e,
0xbdf5bdff,0x3d153c49,0x3d153c49,0x3df53dff,0xbdc6bde2,0x3da23d71,0x3da23d71,0x3dc63de2,0xbd71bda2,0x3de23dc6,0x3de23dc6,0x3d713da2,0xbc49bd15,0x3dff3df5,0x3dff3df5,0x3c493d15,
0x3e003e00,0,0x3e003e00,0,0x3e003e00,0,0x3e003e00,0,0x3e003e00,0,0x3e003e00,0,0x3e003e00,0,0x3e003e00,0,
0xbdf5bdff,0xbd15bc49,0x3d153c49,0xbdf5bdff,0xbdc6bde2,0xbda2bd71,0x3da23d71,0xbdc6bde2,0xbd71bda2,0xbde2bdc6,0x3de23dc6,0xbd71bda2,0xbc49bd15,0xbdffbdf5,0x3dff3df5,0xbc49bd15,
0x3dd53dfb,0x3d8e3cc8,0xbdd5bdfb,0xbd8ebcc8,0x3cc83d8e,0x3dfb3dd5,0xbcc8bd8e,0xbdfbbdd5,0xbd8ebcc8,0x3dd53dfb,0x3d8e3cc8,0xbdd5bdfb,0xbdfbbdd5,0x3cc83d8e,0x3dfb3dd5,0xbcc8bd8e,
0xbda2bdf5,0xbdc6bd15,0xbdc6bd15,0x3da23df5,0x3d71bc49,0xbde2bdff,0xbde2bdff,0xbd713c49,0x3dff3de2,0x3c49bd71,0x3c49bd71,0xbdffbde2,0x3d153dc6,0x3df53da2,0x3df53da2,0xbd15bdc6,
0x3d443ded,0x3ded3d44,0x3d443ded,0x3ded3d44,0xbdedbd44,0x3d443ded,0xbdedbd44,0x3d443ded,0xbd44bded,0xbdedbd44,0xbd44bded,0xbdedbd44,0x3ded3d44,0xbd44bded,0x3ded3d44,0xbd44bded,
0xbc49bde2,0xbdffbd71,0x3dff3d71,0xbc49bde2,0x3df53dc6,0x3d15bda2,0xbd153da2,0x3df53dc6,0xbda23d15,0x3dc63df5,0xbdc6bdf5,0xbda23d15,0xbd71bdff,0xbde2bc49,0x3de23c49,0xbd71bdff,
0xbcc83dd5,0x3dfb3d8e,0x3cc8bdd5,0xbdfbbd8e,0xbd8ebdfb,0xbdd53cc8,0x3d8e3dfb,0x3dd5bcc8,0x3dfb3d8e,0x3cc8bdd5,0xbdfbbd8e,0xbcc83dd5,0xbdd53cc8,0x3d8e3dfb,0x3dd5bcc8,0xbd8ebdfb,
0x3d71bdc6,0xbde2bda2,0xbde2bda2,0xbd713dc6,0xbc493df5,0x3dff3d15,0x3dff3d15,0x3c49bdf5,0xbd15bdff,0xbdf53c49,0xbdf53c49,0x3d153dff,0x3da23de2,0x3dc6bd71,0x3dc6bd71,0xbda2bde2,
0xbdb53db5,0x3db53db5,0xbdb53db5,0x3db53db5,0x3db5bdb5,0xbdb5bdb5,0x3db5bdb5,0xbdb5bdb5,0xbdb53db5,0x3db53db5,0xbdb53db5,0x3db53db5,0x3db5bdb5,0xbdb5bdb5,0x3db5bdb5,0xbdb5bdb5,
0x3de2bda2,0xbd71bdc6,0x3d713dc6,0x3de2bda2,0xbdff3d15,0x3c493df5,0xbc49bdf5,0xbdff3d15,0x3df53c49,0x3d15bdff,0xbd153dff,0x3df53c49,0xbdc6bd71,0xbda23de2,0x3da2bde2,0xbdc6bd71,
0xbdfb3d8e,0x3cc83dd5,0x3dfbbd8e,0xbcc8bdd5,0x3dd53cc8,0x3d8ebdfb,0xbdd5bcc8,0xbd8e3dfb,0xbcc8bdd5,0xbdfb3d8e,0x3cc83dd5,0x3dfbbd8e,0xbd8e3dfb,0x3dd53cc8,0x3d8ebdfb,0xbdd5bcc8,
0x3dffbd71,0x3c49bde2,0x3c49bde2,0xbdff3d71,0xbd15bda2,0xbdf53dc6,0xbdf53dc6,0x3d153da2,0xbdc63df5,0x3da23d15,0x3da23d15,0x3dc6bdf5,0x3de2bc49,0x3d71bdff,0x3d71bdff,0xbde23c49,
0xbded3d44,0xbd443ded,0xbded3d44,0xbd443ded,0xbd443ded,0x3dedbd44,0xbd443ded,0x3dedbd44,0x3dedbd44,0x3d44bded,0x3dedbd44,0x3d44bded,0x3d44bded,0xbded3d44,0x3d44bded,0xbded3d44,
0x3dc6bd15,0x3da2bdf5,0xbda23df5,0x3dc6bd15,0x3de2bdff,0xbd71bc49,0x3d713c49,0x3de2bdff,0xbc49bd71,0xbdff3de2,0x3dffbde2,0xbc49bd71,0xbdf53da2,0xbd153dc6,0x3d15bdc6,0xbdf53da2,
0xbd8e3cc8,0xbdd53dfb,0x3d8ebcc8,0x3dd5bdfb,0xbdfb3dd5,0xbcc83d8e,0x3dfbbdd5,0x3cc8bd8e,0xbdd53dfb,0x3d8ebcc8,0x3dd5bdfb,0xbd8e3cc8,0xbcc83d8e,0x3dfbbdd5,0x3cc8bd8e,0xbdfb3dd5,
0x3d15bc49,0x3df5bdff,0x3df5bdff,0xbd153c49,0x3da2bd71,0x3dc6bde2,0x3dc6bde2,0xbda23d71,0x3de2bdc6,0x3d71bda2,0x3d71bda2,0xbde23dc6,0x3dffbdf5,0x3c49bd15,0x3c49bd15,0xbdff3df5,
0,0xbe003e00,0,0xbe003e00,0,0xbe003e00,0,0xbe003e00,0,0xbe003e00,0,0xbe003e00,0,0xbe003e00,0,0xbe003e00,
0xbd153c49,0x3df5bdff,0xbdf53dff,0xbd153c49,0xbda23d71,0x3dc6bde2,0xbdc63de2,0xbda23d71,0xbde23dc6,0x3d71bda2,0xbd713da2,0xbde23dc6,0xbdff3df5,0x3c49bd15,0xbc493d15,0xbdff3df5,
0x3d8ebcc8,0xbdd53dfb,0xbd8e3cc8,0x3dd5bdfb,0x3dfbbdd5,0xbcc83d8e,0xbdfb3dd5,0x3cc8bd8e,0x3dd5bdfb,0x3d8ebcc8,0xbdd53dfb,0xbd8e3cc8,0x3cc8bd8e,0x3dfbbdd5,0xbcc83d8e,0xbdfb3dd5,
0xbdc63d15,0x3da2bdf5,0x3da2bdf5,0x3dc6bd15,0xbde23dff,0xbd71bc49,0xbd71bc49,0x3de2bdff,0x3c493d71,0xbdff3de2,0xbdff3de2,0xbc49bd71,0x3df5bda2,0xbd153dc6,0xbd153dc6,0xbdf53da2,
0x3dedbd44,0xbd443ded,0x3dedbd44,0xbd443ded,0x3d44bded,0x3dedbd44,0x3d44bded,0x3dedbd44,0xbded3d44,0x3d44bded,0xbded3d44,0x3d44bded,0xbd443ded,0xbded3d44,0xbd443ded,0xbded3d44,
0xbdff3d71,0x3c49bde2,0xbc493de2,0xbdff3d71,0x3d153da2,0xbdf53dc6,0x3df5bdc6,0x3d153da2,0x3dc6bdf5,0x3da23d15,0xbda2bd15,0x3dc6bdf5,0xbde23c49,0x3d71bdff,0xbd713dff,0xbde23c49,
0x3dfbbd8e,0x3cc83dd5,0xbdfb3d8e,0xbcc8bdd5,0xbdd5bcc8,0x3d8ebdfb,0x3dd53cc8,0xbd8e3dfb,0x3cc83dd5,0xbdfb3d8e,0xbcc8bdd5,0x3dfbbd8e,0x3d8ebdfb,0x3dd53cc8,0xbd8e3dfb,0xbdd5bcc8,
0xbde23da2,0xbd71bdc6,0xbd71bdc6,0x3de2bda2,0x3dffbd15,0x3c493df5,0x3c493df5,0xbdff3d15,0xbdf5bc49,0x3d15bdff,0x3d15bdff,0x3df53c49,0x3dc63d71,0xbda23de2,0xbda23de2,0xbdc6bd71,
0x3db5bdb5,0x3db53db5,0x3db5bdb5,0x3db53db5,0xbdb53db5,0xbdb5bdb5,0xbdb53db5,0xbdb5bdb5,0x3db5bdb5,0x3db53db5,0x3db5bdb5,0x3db53db5,0xbdb53db5,0xbdb5bdb5,0xbdb53db5,0xbdb5bdb5,
0xbd713dc6,0xbde2bda2,0x3de23da2,0xbd713dc6,0x3c49bdf5,0x3dff3d15,0xbdffbd15,0x3c49bdf5,0x3d153dff,0xbdf53c49,0x3df5bc49,0x3d153dff,0xbda2bde2,0x3dc6bd71,0xbdc63d71,0xbda2bde2,
0x3cc8bdd5,0x3dfb3d8e,0xbcc83dd5,0xbdfbbd8e,0x3d8e3dfb,0xbdd53cc8,0xbd8ebdfb,0x3dd5bcc8,0xbdfbbd8e,0x3cc8bdd5,0x3dfb3d8e,0xbcc83dd5,0x3dd5bcc8,0x3d8e3dfb,0xbdd53cc8,0xbd8ebdfb,
0x3c493de2,0xbdffbd71,0xbdffbd71,0xbc49bde2,0xbdf5bdc6,0x3d15bda2,0x3d15bda2,0x3df53dc6,0x3da2bd15,0x3dc63df5,0x3dc63df5,0xbda23d15,0x3d713dff,0xbde2bc49,0xbde2bc49,0xbd71bdff,
0xbd44bded,0x3ded3d44,0xbd44bded,0x3ded3d44,0x3ded3d44,0x3d443ded,0x3ded3d44,0x3d443ded,0x3d443ded,0xbdedbd44,0x3d443ded,0xbdedbd44,0xbdedbd44,0xbd44bded,0xbdedbd44,0xbd44bded,
0x3da23df5,0xbdc6bd15,0x3dc63d15,0x3da23df5,0xbd713c49,0xbde2bdff,0x3de23dff,0xbd713c49,0xbdffbde2,0x3c49bd71,0xbc493d71,0xbdffbde2,0xbd15bdc6,0x3df53da2,0xbdf5bda2,0xbd15bdc6,
0xbdd5bdfb,0x3d8e3cc8,0x3dd53dfb,0xbd8ebcc8,0xbcc8bd8e,0x3dfb3dd5,0x3cc83d8e,0xbdfbbdd5,0x3d8e3cc8,0x3dd53dfb,0xbd8ebcc8,0xbdd5bdfb,0x3dfb3dd5,0x3cc83d8e,0xbdfbbdd5,0xbcc8bd8e,
0x3df53dff,0xbd15bc49,0xbd15bc49,0xbdf5bdff,0x3dc63de2,0xbda2bd71,0xbda2bd71,0xbdc6bde2,0x3d713da2,0xbde2bdc6,0xbde2bdc6,0xbd71bda2,0x3c493d15,0xbdffbdf5,0xbdffbdf5,0xbc49bd15,
0x80008000,0x3e003e00,0x80008000,0x3e003e00,0x80008000,0x3e003e00,0x80008000,0x3e003e00,0x80008000,0x3e003e00,0x80008000,0x3e003e00,0x80008000,0x3e003e00,0x80008000,0x3e003e00,
0xbd15bc49,0x3df53dff,0xbdf5bdff,0xbd15bc49,0xbda2bd71,0x3dc63de2,0xbdc6bde2,0xbda2bd71,0xbde2bdc6,0x3d713da2,0xbd71bda2,0xbde2bdc6,0xbdffbdf5,0x3c493d15,0xbc49bd15,0xbdffbdf5,
0xbd8ebcc8,0x3dd53dfb,0x3d8e3cc8,0xbdd5bdfb,0xbdfbbdd5,0x3cc83d8e,0x3dfb3dd5,0xbcc8bd8e,0xbdd5bdfb,0xbd8ebcc8,0x3dd53dfb,0x3d8e3cc8,0xbcc8bd8e,0xbdfbbdd5,0x3cc83d8e,0x3dfb3dd5,
0xbdc6bd15,0x3da23df5,0x3da23df5,0x3dc63d15,0xbde2bdff,0xbd713c49,0xbd713c49,0x3de23dff,0x3c49bd71,0xbdffbde2,0xbdffbde2,0xbc493d71,0x3df53da2,0xbd15bdc6,0xbd15bdc6,0xbdf5bda2,
0xbdedbd44,0x3d443ded,0xbdedbd44,0x3d443ded,0xbd44bded,0xbdedbd44,0xbd44bded,0xbdedbd44,0x3ded3d44,0xbd44bded,0x3ded3d44,0xbd44bded,0x3d443ded,0x3ded3d44,0x3d443ded,0x3ded3d44,
0xbdffbd71,0x3c493de2,0xbc49bde2,0xbdffbd71,0x3d15bda2,0xbdf5bdc6,0x3df53dc6,0x3d15bda2,0x3dc63df5,0x3da2bd15,0xbda23d15,0x3dc63df5,0xbde2bc49,0x3d713dff,0xbd71bdff,0xbde2bc49,
0xbdfbbd8e,0xbcc83dd5,0x3dfb3d8e,0x3cc8bdd5,0x3dd5bcc8,0xbd8ebdfb,0xbdd53cc8,0x3d8e3dfb,0xbcc83dd5,0x3dfb3d8e,0x3cc8bdd5,0xbdfbbd8e,0xbd8ebdfb,0xbdd53cc8,0x3d8e3dfb,0x3dd5bcc8,
0xbde2bda2,0xbd713dc6,0xbd713dc6,0x3de23da2,0x3dff3d15,0x3c49bdf5,0x3c49bdf5,0xbdffbd15,0xbdf53c49,0x3d153dff,0x3d153dff,0x3df5bc49,0x3dc6bd71,0xbda2bde2,0xbda2bde2,0xbdc63d71,
0xbdb5bdb5,0xbdb53db5,0xbdb5bdb5,0xbdb53db5,0x3db53db5,0x3db5bdb5,0x3db53db5,0x3db5bdb5,0xbdb5bdb5,0xbdb53db5,0xbdb5bdb5,0xbdb53db5,0x3db53db5,0x3db5bdb5,0x3db53db5,0x3db5bdb5,
0xbd71bdc6,0xbde23da2,0x3de2bda2,0xbd71bdc6,0x3c493df5,0x3dffbd15,0xbdff3d15,0x3c493df5,0x3d15bdff,0xbdf5bc49,0x3df53c49,0x3d15bdff,0xbda23de2,0x3dc63d71,0xbdc6bd71,0xbda23de2,
0xbcc8bdd5,0xbdfb3d8e,0x3cc83dd5,0x3dfbbd8e,0xbd8e3dfb,0x3dd53cc8,0x3d8ebdfb,0xbdd5bcc8,0x3dfbbd8e,0xbcc8bdd5,0xbdfb3d8e,0x3cc83dd5,0xbdd5bcc8,0xbd8e3dfb,0x3dd53cc8,0x3d8ebdfb,
0x3c49bde2,0xbdff3d71,0xbdff3d71,0xbc493de2,0xbdf53dc6,0x3d153da2,0x3d153da2,0x3df5bdc6,0x3da23d15,0x3dc6bdf5,0x3dc6bdf5,0xbda2bd15,0x3d71bdff,0xbde23c49,0xbde23c49,0xbd713dff,
0x3d44bded,0xbded3d44,0x3d44bded,0xbded3d44,0xbded3d44,0xbd443ded,0xbded3d44,0xbd443ded,0xbd443ded,0x3dedbd44,0xbd443ded,0x3dedbd44,0x3dedbd44,0x3d44bded,0x3dedbd44,0x3d44bded,
0x3da2bdf5,0xbdc63d15,0x3dc6bd15,0x3da2bdf5,0xbd71bc49,0xbde23dff,0x3de2bdff,0xbd71bc49,0xbdff3de2,0x3c493d71,0xbc49bd71,0xbdff3de2,0xbd153dc6,0x3df5bda2,0xbdf53da2,0xbd153dc6,
0x3dd5bdfb,0xbd8e3cc8,0xbdd53dfb,0x3d8ebcc8,0x3cc8bd8e,0xbdfb3dd5,0xbcc83d8e,0x3dfbbdd5,0xbd8e3cc8,0xbdd53dfb,0x3d8ebcc8,0x3dd5bdfb,0xbdfb3dd5,0xbcc83d8e,0x3dfbbdd5,0x3cc8bd8e,
0x3df5bdff,0xbd153c49,0xbd153c49,0xbdf53dff,0x3dc6bde2,0xbda23d71,0xbda23d71,0xbdc63de2,0x3d71bda2,0xbde23dc6,0xbde23dc6,0xbd713da2,0x3c49bd15,0xbdff3df5,0xbdff3df5,0xbc493d15,
0x3e00be00,0,0x3e00be00,0,0x3e00be00,0,0x3e00be00,0,0x3e00be00,0,0x3e00be00,0,0x3e00be00,0,0x3e00be00,0,
0x3df5bdff,0x3d15bc49,0xbd153c49,0x3df5bdff,0x3dc6bde2,0x3da2bd71,0xbda23d71,0x3dc6bde2,0x3d71bda2,0x3de2bdc6,0xbde23dc6,0x3d71bda2,0x3c49bd15,0x3dffbdf5,0xbdff3df5,0x3c49bd15,
0x3dd5bdfb,0x3d8ebcc8,0xbdd53dfb,0xbd8e3cc8,0x3cc8bd8e,0x3dfbbdd5,0xbcc83d8e,0xbdfb3dd5,0xbd8e3cc8,0x3dd5bdfb,0x3d8ebcc8,0xbdd53dfb,0xbdfb3dd5,0x3cc8bd8e,0x3dfbbdd5,0xbcc83d8e,
0x3da2bdf5,0x3dc6bd15,0x3dc6bd15,0xbda23df5,0xbd71bc49,0x3de2bdff,0x3de2bdff,0x3d713c49,0xbdff3de2,0xbc49bd71,0xbc49bd71,0x3dffbde2,0xbd153dc6,0xbdf53da2,0xbdf53da2,0x3d15bdc6,
0x3d44bded,0x3dedbd44,0x3d44bded,0x3dedbd44,0xbded3d44,0x3d44bded,0xbded3d44,0x3d44bded,0xbd443ded,0xbded3d44,0xbd443ded,0xbded3d44,0x3dedbd44,0xbd443ded,0x3dedbd44,0xbd443ded,
0x3c49bde2,0x3dffbd71,0xbdff3d71,0x3c49bde2,0xbdf53dc6,0xbd15bda2,0x3d153da2,0xbdf53dc6,0x3da23d15,0xbdc63df5,0x3dc6bdf5,0x3da23d15,0x3d71bdff,0x3de2bc49,0xbde23c49,0x3d71bdff,
0xbcc8bdd5,0x3dfbbd8e,0x3cc83dd5,0xbdfb3d8e,0xbd8e3dfb,0xbdd5bcc8,0x3d8ebdfb,0x3dd53cc8,0x3dfbbd8e,0x3cc83dd5,0xbdfb3d8e,0xbcc8bdd5,0xbdd5bcc8,0x3d8ebdfb,0x3dd53cc8,0xbd8e3dfb,
0xbd71bdc6,0x3de2bda2,0x3de2bda2,0x3d713dc6,0x3c493df5,0xbdff3d15,0xbdff3d15,0xbc49bdf5,0x3d15bdff,0x3df53c49,0x3df53c49,0xbd153dff,0xbda23de2,0xbdc6bd71,0xbdc6bd71,0x3da2bde2,
0xbdb5bdb5,0x3db5bdb5,0xbdb5bdb5,0x3db5bdb5,0x3db53db5,0xbdb53db5,0x3db53db5,0xbdb53db5,0xbdb5bdb5,0x3db5bdb5,0xbdb5bdb5,0x3db5bdb5,0x3db53db5,0xbdb53db5,0x3db53db5,0xbdb53db5,
0xbde2bda2,0x3d71bdc6,0xbd713dc6,0xbde2bda2,0x3dff3d15,0xbc493df5,0x3c49bdf5,0x3dff3d15,0xbdf53c49,0xbd15bdff,0x3d153dff,0xbdf53c49,0x3dc6bd71,0x3da23de2,0xbda2bde2,0x3dc6bd71,
0xbdfbbd8e,0x3cc8bdd5,0x3dfb3d8e,0xbcc83dd5,0x3dd5bcc8,0x3d8e3dfb,0xbdd53cc8,0xbd8ebdfb,0xbcc83dd5,0xbdfbbd8e,0x3cc8bdd5,0x3dfb3d8e,0xbd8ebdfb,0x3dd5bcc8,0x3d8e3dfb,0xbdd53cc8,
0xbdffbd71,0xbc49bde2,0xbc49bde2,0x3dff3d71,0x3d15bda2,0x3df53dc6,0x3df53dc6,0xbd153da2,0x3dc63df5,0xbda23d15,0xbda23d15,0xbdc6bdf5,0xbde2bc49,0xbd71bdff,0xbd71bdff,0x3de23c49,
0xbdedbd44,0xbd44bded,0xbdedbd44,0xbd44bded,0xbd44bded,0x3ded3d44,0xbd44bded,0x3ded3d44,0x3ded3d44,0x3d443ded,0x3ded3d44,0x3d443ded,0x3d443ded,0xbdedbd44,0x3d443ded,0xbdedbd44,
0xbdc6bd15,0xbda2bdf5,0x3da23df5,0xbdc6bd15,0xbde2bdff,0x3d71bc49,0xbd713c49,0xbde2bdff,0x3c49bd71,0x3dff3de2,0xbdffbde2,0x3c49bd71,0x3df53da2,0x3d153dc6,0xbd15bdc6,0x3df53da2,
0xbd8ebcc8,0xbdd5bdfb,0x3d8e3cc8,0x3dd53dfb,0xbdfbbdd5,0xbcc8bd8e,0x3dfb3dd5,0x3cc83d8e,0xbdd5bdfb,0x3d8e3cc8,0x3dd53dfb,0xbd8ebcc8,0xbcc8bd8e,0x3dfb3dd5,0x3cc83d8e,0xbdfbbdd5,
0xbd15bc49,0xbdf5bdff,0xbdf5bdff,0x3d153c49,0xbda2bd71,0xbdc6bde2,0xbdc6bde2,0x3da23d71,0xbde2bdc6,0xbd71bda2,0xbd71bda2,0x3de23dc6,0xbdffbdf5,0xbc49bd15,0xbc49bd15,0x3dff3df5,
0x80008000,0x3e003e00,0x80008000,0x3e003e00,0x80008000,0x3e003e00,0x80008000,0x3e003e00,0x80008000,0x3e003e00,0x80008000,0x3e003e00,0x80008000,0x3e003e00,0x80008000,0x3e003e00,
0x3d153c49,0xbdf5bdff,0x3df53dff,0x3d153c49,0x3da23d71,0xbdc6bde2,0x3dc63de2,0x3da23d71,0x3de23dc6,0xbd71bda2,0x3d713da2,0x3de23dc6,0x3dff3df5,0xbc49bd15,0x3c493d15,0x3dff3df5,
0xbd8ebcc8,0x3dd53dfb,0x3d8e3cc8,0xbdd5bdfb,0xbdfbbdd5,0x3cc83d8e,0x3dfb3dd5,0xbcc8bd8e,0xbdd5bdfb,0xbd8ebcc8,0x3dd53dfb,0x3d8e3cc8,0xbcc8bd8e,0xbdfbbdd5,0x3cc83d8e,0x3dfb3dd5,
0x3dc63d15,0xbda2bdf5,0xbda2bdf5,0xbdc6bd15,0x3de23dff,0x3d71bc49,0x3d71bc49,0xbde2bdff,0xbc493d71,0x3dff3de2,0x3dff3de2,0x3c49bd71,0xbdf5bda2,0x3d153dc6,0x3d153dc6,0x3df53da2,
0xbdedbd44,0x3d443ded,0xbdedbd44,0x3d443ded,0xbd44bded,0xbdedbd44,0xbd44bded,0xbdedbd44,0x3ded3d44,0xbd44bded,0x3ded3d44,0xbd44bded,0x3d443ded,0x3ded3d44,0x3d443ded,0x3ded3d44,
0x3dff3d71,0xbc49bde2,0x3c493de2,0x3dff3d71,0xbd153da2,0x3df53dc6,0xbdf5bdc6,0xbd153da2,0xbdc6bdf5,0xbda23d15,0x3da2bd15,0xbdc6bdf5,0x3de23c49,0xbd71bdff,0x3d713dff,0x3de23c49,
0xbdfbbd8e,0xbcc83dd5,0x3dfb3d8e,0x3cc8bdd5,0x3dd5bcc8,0xbd8ebdfb,0xbdd53cc8,0x3d8e3dfb,0xbcc83dd5,0x3dfb3d8e,0x3cc8bdd5,0xbdfbbd8e,0xbd8ebdfb,0xbdd53cc8,0x3d8e3dfb,0x3dd5bcc8,
0x3de23da2,0x3d71bdc6,0x3d71bdc6,0xbde2bda2,0xbdffbd15,0xbc493df5,0xbc493df5,0x3dff3d15,0x3df5bc49,0xbd15bdff,0xbd15bdff,0xbdf53c49,0xbdc63d71,0x3da23de2,0x3da23de2,0x3dc6bd71,
0xbdb5bdb5,0xbdb53db5,0xbdb5bdb5,0xbdb53db5,0x3db53db5,0x3db5bdb5,0x3db53db5,0x3db5bdb5,0xbdb5bdb5,0xbdb53db5,0xbdb5bdb5,0xbdb53db5,0x3db53db5,0x3db5bdb5,0x3db53db5,0x3db5bdb5,
0x3d713dc6,0x3de2bda2,0xbde23da2,0x3d713dc6,0xbc49bdf5,0xbdff3d15,0x3dffbd15,0xbc49bdf5,0xbd153dff,0x3df53c49,0xbdf5bc49,0xbd153dff,0x3da2bde2,0xbdc6bd71,0x3dc63d71,0x3da2bde2,
0xbcc8bdd5,0xbdfb3d8e,0x3cc83dd5,0x3dfbbd8e,0xbd8e3dfb,0x3dd53cc8,0x3d8ebdfb,0xbdd5bcc8,0x3dfbbd8e,0xbcc8bdd5,0xbdfb3d8e,0x3cc83dd5,0xbdd5bcc8,0xbd8e3dfb,0x3dd53cc8,0x3d8ebdfb,
0xbc493de2,0x3dffbd71,0x3dffbd71,0x3c49bde2,0x3df5bdc6,0xbd15bda2,0xbd15bda2,0xbdf53dc6,0xbda2bd15,0xbdc63df5,0xbdc63df5,0x3da23d15,0xbd713dff,0x3de2bc49,0x3de2bc49,0x3d71bdff,
0x3d44bded,0xbded3d44,0x3d44bded,0xbded3d44,0xbded3d44,0xbd443ded,0xbded3d44,0xbd443ded,0xbd443ded,0x3dedbd44,0xbd443ded,0x3dedbd44,0x3dedbd44,0x3d44bded,0x3dedbd44,0x3d44bded,
0xbda23df5,0x3dc6bd15,0xbdc63d15,0xbda23df5,0x3d713c49,0x3de2bdff,0xbde23dff,0x3d713c49,0x3dffbde2,0xbc49bd71,0x3c493d71,0x3dffbde2,0x3d15bdc6,0xbdf53da2,0x3df5bda2,0x3d15bdc6,
0x3dd5bdfb,0xbd8e3cc8,0xbdd53dfb,0x3d8ebcc8,0x3cc8bd8e,0xbdfb3dd5,0xbcc83d8e,0x3dfbbdd5,0xbd8e3cc8,0xbdd53dfb,0x3d8ebcc8,0x3dd5bdfb,0xbdfb3dd5,0xbcc83d8e,0x3dfbbdd5,0x3cc8bd8e,
0xbdf53dff,0x3d15bc49,0x3d15bc49,0x3df5bdff,0xbdc63de2,0x3da2bd71,0x3da2bd71,0x3dc6bde2,0xbd713da2,0x3de2bdc6,0x3de2bdc6,0x3d71bda2,0xbc493d15,0x3dffbdf5,0x3dffbdf5,0x3c49bd15,
0x3e00be00,0,0x3e00be00,0,0x3e00be00,0,0x3e00be00,0,0x3e00be00,0,0x3e00be00,0,0x3e00be00,0,0x3e00be00,0,
0xbdf53dff,0xbd153c49,0x3d15bc49,0xbdf53dff,0xbdc63de2,0xbda23d71,0x3da2bd71,0xbdc63de2,0xbd713da2,0xbde23dc6,0x3de2bdc6,0xbd713da2,0xbc493d15,0xbdff3df5,0x3dffbdf5,0xbc493d15,
0x3dd5bdfb,0x3d8ebcc8,0xbdd53dfb,0xbd8e3cc8,0x3cc8bd8e,0x3dfbbdd5,0xbcc83d8e,0xbdfb3dd5,0xbd8e3cc8,0x3dd5bdfb,0x3d8ebcc8,0xbdd53dfb,0xbdfb3dd5,0x3cc8bd8e,0x3dfbbdd5,0xbcc83d8e,
0xbda23df5,0xbdc63d15,0xbdc63d15,0x3da2bdf5,0x3d713c49,0xbde23dff,0xbde23dff,0xbd71bc49,0x3dffbde2,0x3c493d71,0x3c493d71,0xbdff3de2,0x3d15bdc6,0x3df5bda2,0x3df5bda2,0xbd153dc6,
0x3d44bded,0x3dedbd44,0x3d44bded,0x3dedbd44,0xbded3d44,0x3d44bded,0xbded3d44,0x3d44bded,0xbd443ded,0xbded3d44,0xbd443ded,0xbded3d44,0x3dedbd44,0xbd443ded,0x3dedbd44,0xbd443ded,
0xbc493de2,0xbdff3d71,0x3dffbd71,0xbc493de2,0x3df5bdc6,0x3d153da2,0xbd15bda2,0x3df5bdc6,0xbda2bd15,0x3dc6bdf5,0xbdc63df5,0xbda2bd15,0xbd713dff,0xbde23c49,0x3de2bc49,0xbd713dff,
0xbcc8bdd5,0x3dfbbd8e,0x3cc83dd5,0xbdfb3d8e,0xbd8e3dfb,0xbdd5bcc8,0x3d8ebdfb,0x3dd53cc8,0x3dfbbd8e,0x3cc83dd5,0xbdfb3d8e,0xbcc8bdd5,0xbdd5bcc8,0x3d8ebdfb,0x3dd53cc8,0xbd8e3dfb,
0x3d713dc6,0xbde23da2,0xbde23da2,0xbd71bdc6,0xbc49bdf5,0x3dffbd15,0x3dffbd15,0x3c493df5,0xbd153dff,0xbdf5bc49,0xbdf5bc49,0x3d15bdff,0x3da2bde2,0x3dc63d71,0x3dc63d71,0xbda23de2,
0xbdb5bdb5,0x3db5bdb5,0xbdb5bdb5,0x3db5bdb5,0x3db53db5,0xbdb53db5,0x3db53db5,0xbdb53db5,0xbdb5bdb5,0x3db5bdb5,0xbdb5bdb5,0x3db5bdb5,0x3db53db5,0xbdb53db5,0x3db53db5,0xbdb53db5,
0x3de23da2,0xbd713dc6,0x3d71bdc6,0x3de23da2,0xbdffbd15,0x3c49bdf5,0xbc493df5,0xbdffbd15,0x3df5bc49,0x3d153dff,0xbd15bdff,0x3df5bc49,0xbdc63d71,0xbda2bde2,0x3da23de2,0xbdc63d71,
0xbdfbbd8e,0x3cc8bdd5,0x3dfb3d8e,0xbcc83dd5,0x3dd5bcc8,0x3d8e3dfb,0xbdd53cc8,0xbd8ebdfb,0xbcc83dd5,0xbdfbbd8e,0x3cc8bdd5,0x3dfb3d8e,0xbd8ebdfb,0x3dd5bcc8,0x3d8e3dfb,0xbdd53cc8,
0x3dff3d71,0x3c493de2,0x3c493de2,0xbdffbd71,0xbd153da2,0xbdf5bdc6,0xbdf5bdc6,0x3d15bda2,0xbdc6bdf5,0x3da2bd15,0x3da2bd15,0x3dc63df5,0x3de23c49,0x3d713dff,0x3d713dff,0xbde2bc49,
0xbdedbd44,0xbd44bded,0xbdedbd44,0xbd44bded,0xbd44bded,0x3ded3d44,0xbd44bded,0x3ded3d44,0x3ded3d44,0x3d443ded,0x3ded3d44,0x3d443ded,0x3d443ded,0xbdedbd44,0x3d443ded,0xbdedbd44,
0x3dc63d15,0x3da23df5,0xbda2bdf5,0x3dc63d15,0x3de23dff,0xbd713c49,0x3d71bc49,0x3de23dff,0xbc493d71,0xbdffbde2,0x3dff3de2,0xbc493d71,0xbdf5bda2,0xbd15bdc6,0x3d153dc6,0xbdf5bda2,
0xbd8ebcc8,0xbdd5bdfb,0x3d8e3cc8,0x3dd53dfb,0xbdfbbdd5,0xbcc8bd8e,0x3dfb3dd5,0x3cc83d8e,0xbdd5bdfb,0x3d8e3cc8,0x3dd53dfb,0xbd8ebcc8,0xbcc8bd8e,0x3dfb3dd5,0x3cc83d8e,0xbdfbbdd5,
0x3d153c49,0x3df53dff,0x3df53dff,0xbd15bc49,0x3da23d71,0x3dc63de2,0x3dc63de2,0xbda2bd71,0x3de23dc6,0x3d713da2,0x3d713da2,0xbde2bdc6,0x3dff3df5,0x3c493d15,0x3c493d15,0xbdffbdf5,
0x80003e00,0x3e000000,0x80003e00,0x3e000000,0x80003e00,0x3e000000,0x80003e00,0x3e000000,0x80003e00,0x3e000000,0x80003e00,0x3e000000,0x80003e00,0x3e000000,0x80003e00,0x3e000000,
0x80003e00,0x3e000000,0xbdb53db5,0x3db53db5,0xbcc83dfb,0x3dfb3cc8,0xbdd53d8e,0x3d8e3dd5,0xbd443ded,0x3ded3d44,0xbded3d44,0x3d443ded,0xbd8e3dd5,0x3dd53d8e,0xbdfb3cc8,0x3cc83dfb,
0x80003e00,0x3e000000,0xbe000000,0x3e00,0xbd443ded,0x3ded3d44,0xbdedbd44,0xbd443ded,0xbdb53db5,0x3db53db5,0xbdb5bdb5,0xbdb53db5,0xbded3d44,0x3d443ded,0xbd44bded,0xbded3d44,
0x80003e00,0x3e000000,0xbdb5bdb5,0xbdb53db5,0xbd8e3dd5,0x3dd53d8e,0xbcc8bdfb,0xbdfb3cc8,0xbded3d44,0x3d443ded,0x3d44bded,0xbdedbd44,0xbdfbbcc8,0xbcc83dfb,0x3dd5bd8e,0xbd8ebdd5,
0x80003e00,0x3e000000,0x8000be00,0xbe000000,0xbdb53db5,0x3db53db5,0x3db5bdb5,0xbdb5bdb5,0xbe000000,0x3e00,0x3e000000,0xbe00,0xbdb5bdb5,0xbdb53db5,0x3db53db5,0x3db5bdb5,
0x80003e00,0x3e000000,0x3db5bdb5,0xbdb5bdb5,0xbdd53d8e,0x3d8e3dd5,0x3dfb3cc8,0x3cc8bdfb,0xbdedbd44,0xbd443ded,0x3d443ded,0x3dedbd44,0xbcc8bdfb,0xbdfb3cc8,0xbd8e3dd5,0x3dd53d8e,
0x80003e00,0x3e000000,0x3e000000,0xbe00,0xbded3d44,0x3d443ded,0x3d443ded,0x3dedbd44,0xbdb5bdb5,0xbdb53db5,0xbdb53db5,0x3db53db5,0x3d44bded,0xbdedbd44,0xbdedbd44,0xbd443ded,
0x80003e00,0x3e000000,0x3db53db5,0x3db5bdb5,0xbdfb3cc8,0x3cc83dfb,0xbd8e3dd5,0x3dd53d8e,0xbd44bded,0xbded3d44,0xbdedbd44,0xbd443ded,0x3dd5bd8e,0xbd8ebdd5,0x3cc8bdfb,0xbdfbbcc8,
0x80003e00,0x3e000000,0x80003e00,0x3e000000,0xbe000000,0x3e00,0xbe000000,0x3e00,0x8000be00,0xbe000000,0x8000be00,0xbe000000,0x3e000000,0xbe00,0x3e000000,0xbe00,
0x80003e00,0x3e000000,0xbdb53db5,0x3db53db5,0xbdfbbcc8,0xbcc83dfb,0xbd8ebdd5,0xbdd53d8e,0x3d44bded,0xbdedbd44,0x3dedbd44,0xbd44bded,0x3dd53d8e,0x3d8ebdd5,0x3cc83dfb,0x3dfbbcc8,
0x80003e00,0x3e000000,0xbe000000,0x3e00,0xbdedbd44,0xbd443ded,0x3d44bded,0xbdedbd44,0x3db5bdb5,0xbdb5bdb5,0x3db53db5,0x3db5bdb5,0x3d443ded,0x3dedbd44,0xbded3d44,0x3d443ded,
0x80003e00,0x3e000000,0xbdb5bdb5,0xbdb53db5,0xbdd5bd8e,0xbd8e3dd5,0x3dfbbcc8,0xbcc8bdfb,0x3dedbd44,0xbd44bded,0xbd443ded,0x3ded3d44,0xbcc83dfb,0x3dfb3cc8,0xbd8ebdd5,0xbdd53d8e,
0x80003e00,0x3e000000,0x8000be00,0xbe000000,0xbdb5bdb5,0xbdb53db5,0x3db53db5,0x3db5bdb5,0x3e000000,0xbe00,0xbe000000,0x3e00,0xbdb53db5,0x3db53db5,0x3db5bdb5,0xbdb5bdb5,
0x80003e00,0x3e000000,0x3db5bdb5,0xbdb5bdb5,0xbd8ebdd5,0xbdd53d8e,0xbcc83dfb,0x3dfb3cc8,0x3ded3d44,0x3d44bded,0xbd44bded,0xbded3d44,0xbdfb3cc8,0x3cc83dfb,0x3dd53d8e,0x3d8ebdd5,
0x80003e00,0x3e000000,0x3e000000,0xbe00,0xbd44bded,0xbded3d44,0xbded3d44,0x3d443ded,0x3db53db5,0x3db5bdb5,0x3db5bdb5,0xbdb5bdb5,0xbdedbd44,0xbd443ded,0xbd443ded,0x3ded3d44,
0x80003e00,0x3e000000,0x3db53db5,0x3db5bdb5,0xbcc8bdfb,0xbdfb3cc8,0xbdd5bd8e,0xbd8e3dd5,0x3d443ded,0x3dedbd44,0x3ded3d44,0x3d44bded,0xbd8ebdd5,0xbdd53d8e,0xbdfbbcc8,0xbcc83dfb,
0x80003e00,0x3e000000,0x80003e00,0x3e000000,0x8000be00,0xbe000000,0x8000be00,0xbe000000,0x80003e00,0x3e000000,0x80003e00,0x3e000000,0x8000be00,0xbe000000,0x8000be00,0xbe000000,
0x80003e00,0x3e000000,0xbdb53db5,0x3db53db5,0x3cc8bdfb,0xbdfbbcc8,0x3dd5bd8e,0xbd8ebdd5,0xbd443ded,0x3ded3d44,0xbded3d44,0x3d443ded,0x3d8ebdd5,0xbdd5bd8e,0x3dfbbcc8,0xbcc8bdfb,
0x80003e00,0x3e000000,0xbe000000,0x3e00,0x3d44bded,0xbdedbd44,0x3ded3d44,0x3d44bded,0xbdb53db5,0x3db53db5,0xbdb5bdb5,0xbdb53db5,0x3dedbd44,0xbd44bded,0x3d443ded,0x3dedbd44,
0x80003e00,0x3e000000,0xbdb5bdb5,0xbdb53db5,0x3d8ebdd5,0xbdd5bd8e,0x3cc83dfb,0x3dfbbcc8,0xbded3d44,0x3d443ded,0x3d44bded,0xbdedbd44,0x3dfb3cc8,0x3cc8bdfb,0xbdd53d8e,0x3d8e3dd5,
0x80003e00,0x3e000000,0x8000be00,0xbe000000,0x3db5bdb5,0xbdb5bdb5,0xbdb53db5,0x3db53db5,0xbe000000,0x3e00,0x3e000000,0xbe00,0x3db53db5,0x3db5bdb5,0xbdb5bdb5,0xbdb53db5,
0x80003e00,0x3e000000,0x3db5bdb5,0xbdb5bdb5,0x3dd5bd8e,0xbd8ebdd5,0xbdfbbcc8,0xbcc83dfb,0xbdedbd44,0xbd443ded,0x3d443ded,0x3dedbd44,0x3cc83dfb,0x3dfbbcc8,0x3d8ebdd5,0xbdd5bd8e,
0x80003e00,0x3e000000,0x3e000000,0xbe00,0x3dedbd44,0xbd44bded,0xbd44bded,0xbded3d44,0xbdb5bdb5,0xbdb53db5,0xbdb53db5,0x3db53db5,0xbd443ded,0x3ded3d44,0x3ded3d44,0x3d44bded,
0x80003e00,0x3e000000,0x3db53db5,0x3db5bdb5,0x3dfbbcc8,0xbcc8bdfb,0x3d8ebdd5,0xbdd5bd8e,0xbd44bded,0xbded3d44,0xbdedbd44,0xbd443ded,0xbdd53d8e,0x3d8e3dd5,0xbcc83dfb,0x3dfb3cc8,
0x80003e00,0x3e000000,0x80003e00,0x3e000000,0x3e000000,0xbe00,0x3e000000,0xbe00,0x8000be00,0xbe000000,0x8000be00,0xbe000000,0xbe000000,0x3e00,0xbe000000,0x3e00,
0x80003e00,0x3e000000,0xbdb53db5,0x3db53db5,0x3dfb3cc8,0x3cc8bdfb,0x3d8e3dd5,0x3dd5bd8e,0x3d44bded,0xbdedbd44,0x3dedbd44,0xbd44bded,0xbdd5bd8e,0xbd8e3dd5,0xbcc8bdfb,0xbdfb3cc8,
0x80003e00,0x3e000000,0xbe000000,0x3e00,0x3ded3d44,0x3d44bded,0xbd443ded,0x3ded3d44,0x3db5bdb5,0xbdb5bdb5,0x3db53db5,0x3db5bdb5,0xbd44bded,0xbded3d44,0x3dedbd44,0xbd44bded,
0x80003e00,0x3e000000,0xbdb5bdb5,0xbdb53db5,0x3dd53d8e,0x3d8ebdd5,0xbdfb3cc8,0x3cc83dfb,0x3dedbd44,0xbd44bded,0xbd443ded,0x3ded3d44,0x3cc8bdfb,0xbdfbbcc8,0x3d8e3dd5,0x3dd5bd8e,
0x80003e00,0x3e000000,0x8000be00,0xbe000000,0x3db53db5,0x3db5bdb5,0xbdb5bdb5,0xbdb53db5,0x3e000000,0xbe00,0xbe000000,0x3e00,0x3db5bdb5,0xbdb5bdb5,0xbdb53db5,0x3db53db5,
0x80003e00,0x3e000000,0x3db5bdb5,0xbdb5bdb5,0x3d8e3dd5,0x3dd5bd8e,0x3cc8bdfb,0xbdfbbcc8,0x3ded3d44,0x3d44bded,0xbd44bded,0xbded3d44,0x3dfbbcc8,0xbcc8bdfb,0xbdd5bd8e,0xbd8e3dd5,
0x80003e00,0x3e000000,0x3e000000,0xbe00,0x3d443ded,0x3dedbd44,0x3dedbd44,0xbd44bded,0x3db53db5,0x3db5bdb5,0x3db5bdb5,0xbdb5bdb5,0x3ded3d44,0x3d44bded,0x3d44bded,0xbdedbd44,
0x80003e00,0x3e000000,0x3db53db5,0x3db5bdb5,0x3cc83dfb,0x3dfbbcc8,0x3dd53d8e,0x3d8ebdd5,0x3d443ded,0x3dedbd44,0x3ded3d44,0x3d44bded,0x3d8e3dd5,0x3dd5bd8e,0x3dfb3cc8,0x3cc8bdfb,
0x80003e00,0x3e000000,0x80003e00,0x3e000000,0x80003e00,0x3e000000,0x80003e00,0x3e000000,0x80003e00,0x3e000000,0x80003e00,0x3e000000,0x80003e00,0x3e000000,0x80003e00,0x3e000000,
0xbe000000,0x3e00,0xbdb5bdb5,0xbdb53db5,0xbdfbbcc8,0xbcc83dfb,0xbd8ebdd5,0xbdd53d8e,0xbdedbd44,0xbd443ded,0xbd44bded,0xbded3d44,0xbdd5bd8e,0xbd8e3dd5,0xbcc8bdfb,0xbdfb3cc8,
0x8000be00,0xbe000000,0x3e000000,0xbe00,0x3d44bded,0xbdedbd44,0x3ded3d44,0x3d44bded,0x3db5bdb5,0xbdb5bdb5,0x3db53db5,0x3db5bdb5,0x3dedbd44,0xbd44bded,0x3d443ded,0x3dedbd44,
0x3e000000,0xbe00,0xbdb53db5,0x3db53db5,0x3dd53d8e,0x3d8ebdd5,0xbdfb3cc8,0x3cc83dfb,0x3d443ded,0x3dedbd44,0xbdedbd44,0xbd443ded,0xbcc83dfb,0x3dfb3cc8,0xbd8ebdd5,0xbdd53d8e,
0x80003e00,0x3e000000,0x8000be00,0xbe000000,0xbdb53db5,0x3db53db5,0x3db5bdb5,0xbdb5bdb5,0xbe000000,0x3e00,0x3e000000,0xbe00,0xbdb5bdb5,0xbdb53db5,0x3db53db5,0x3db5bdb5,
0xbe000000,0x3e00,0x3db53db5,0x3db5bdb5,0xbd8ebdd5,0xbdd53d8e,0xbcc83dfb,0x3dfb3cc8,0x3d44bded,0xbdedbd44,0xbded3d44,0x3d443ded,0x3dfbbcc8,0xbcc8bdfb,0xbdd5bd8e,0xbd8e3dd5,
0x8000be00,0xbe000000,0xbe000000,0x3e00,0x3dedbd44,0xbd44bded,0xbd44bded,0xbded3d44,0x3db53db5,0x3db5bdb5,0x3db5bdb5,0xbdb5bdb5,0xbd443ded,0x3ded3d44,0x3ded3d44,0x3d44bded,
0x3e000000,0xbe00,0x3db5bdb5,0xbdb5bdb5,0x3cc83dfb,0x3dfbbcc8,0x3dd53d8e,0x3d8ebdd5,0xbded3d44,0x3d443ded,0xbd443ded,0x3ded3d44,0xbd8ebdd5,0xbdd53d8e,0xbdfbbcc8,0xbcc83dfb,
0x80003e00,0x3e000000,0x80003e00,0x3e000000,0xbe000000,0x3e00,0xbe000000,0x3e00,0x8000be00,0xbe000000,0x8000be00,0xbe000000,0x3e000000,0xbe00,0x3e000000,0xbe00,
0xbe000000,0x3e00,0xbdb5bdb5,0xbdb53db5,0x3cc8bdfb,0xbdfbbcc8,0x3dd5bd8e,0xbd8ebdd5,0x3ded3d44,0x3d44bded,0x3d443ded,0x3dedbd44,0xbd8e3dd5,0x3dd53d8e,0xbdfb3cc8,0x3cc83dfb,
0x8000be00,0xbe000000,0x3e000000,0xbe00,0x3ded3d44,0x3d44bded,0xbd443ded,0x3ded3d44,0xbdb53db5,0x3db53db5,0xbdb5bdb5,0xbdb53db5,0xbd44bded,0xbded3d44,0x3dedbd44,0xbd44bded,
0x3e000000,0xbe00,0xbdb53db5,0x3db53db5,0xbd8e3dd5,0x3dd53d8e,0xbcc8bdfb,0xbdfb3cc8,0xbd44bded,0xbded3d44,0x3ded3d44,0x3d44bded,0x3dfb3cc8,0x3cc8bdfb,0xbdd53d8e,0x3d8e3dd5,
0x80003e00,0x3e000000,0x8000be00,0xbe000000,0xbdb5bdb5,0xbdb53db5,0x3db53db5,0x3db5bdb5,0x3e000000,0xbe00,0xbe000000,0x3e00,0xbdb53db5,0x3db53db5,0x3db5bdb5,0xbdb5bdb5,
0xbe000000,0x3e00,0x3db53db5,0x3db5bdb5,0x3dd5bd8e,0xbd8ebdd5,0xbdfbbcc8,0xbcc83dfb,0xbd443ded,0x3ded3d44,0x3dedbd44,0xbd44bded,0xbcc8bdfb,0xbdfb3cc8,0xbd8e3dd5,0x3dd53d8e,
0x8000be00,0xbe000000,0xbe000000,0x3e00,0x3d443ded,0x3dedbd44,0x3dedbd44,0xbd44bded,0xbdb5bdb5,0xbdb53db5,0xbdb53db5,0x3db53db5,0x3ded3d44,0x3d44bded,0x3d44bded,0xbdedbd44,
0x3e000000,0xbe00,0x3db5bdb5,0xbdb5bdb5,0xbdfb3cc8,0x3cc83dfb,0xbd8e3dd5,0x3dd53d8e,0x3dedbd44,0xbd44bded,0x3d44bded,0xbdedbd44,0xbdd53d8e,0x3d8e3dd5,0xbcc83dfb,0x3dfb3cc8,
0x80003e00,0x3e000000,0x80003e00,0x3e000000,0x8000be00,0xbe000000,0x8000be00,0xbe000000,0x80003e00,0x3e000000,0x80003e00,0x3e000000,0x8000be00,0xbe000000,0x8000be00,0xbe000000,
0xbe000000,0x3e00,0xbdb5bdb5,0xbdb53db5,0x3dfb3cc8,0x3cc8bdfb,0x3d8e3dd5,0x3dd5bd8e,0xbdedbd44,0xbd443ded,0xbd44bded,0xbded3d44,0x3dd53d8e,0x3d8ebdd5,0x3cc83dfb,0x3dfbbcc8,
0x8000be00,0xbe000000,0x3e000000,0xbe00,0xbd443ded,0x3ded3d44,0xbdedbd44,0xbd443ded,0x3db5bdb5,0xbdb5bdb5,0x3db53db5,0x3db5bdb5,0xbded3d44,0x3d443ded,0xbd44bded,0xbded3d44,
0x3e000000,0xbe00,0xbdb53db5,0x3db53db5,0xbdd5bd8e,0xbd8e3dd5,0x3dfbbcc8,0xbcc8bdfb,0x3d443ded,0x3dedbd44,0xbdedbd44,0xbd443ded,0x3cc8bdfb,0xbdfbbcc8,0x3d8e3dd5,0x3dd5bd8e,
0x80003e00,0x3e000000,0x8000be00,0xbe000000,0x3db5bdb5,0xbdb5bdb5,0xbdb53db5,0x3db53db5,0xbe000000,0x3e00,0x3e000000,0xbe00,0x3db53db5,0x3db5bdb5,0xbdb5bdb5,0xbdb53db5,
0xbe000000,0x3e00,0x3db53db5,0x3db5bdb5,0x3d8e3dd5,0x3dd5bd8e,0x3cc8bdfb,0xbdfbbcc8,0x3d44bded,0xbdedbd44,0xbded3d44,0x3d443ded,0xbdfb3cc8,0x3cc83dfb,0x3dd53d8e,0x3d8ebdd5,
0x8000be00,0xbe000000,0xbe000000,0x3e00,0xbded3d44,0x3d443ded,0x3d443ded,0x3dedbd44,0x3db53db5,0x3db5bdb5,0x3db5bdb5,0xbdb5bdb5,0x3d44bded,0xbdedbd44,0xbdedbd44,0xbd443ded,
0x3e000000,0xbe00,0x3db5bdb5,0xbdb5bdb5,0xbcc8bdfb,0xbdfb3cc8,0xbdd5bd8e,0xbd8e3dd5,0xbded3d44,0x3d443ded,0xbd443ded,0x3ded3d44,0x3d8e3dd5,0x3dd5bd8e,0x3dfb3cc8,0x3cc8bdfb,
0x80003e00,0x3e000000,0x80003e00,0x3e000000,0x3e000000,0xbe00,0x3e000000,0xbe00,0x8000be00,0xbe000000,0x8000be00,0xbe000000,0xbe000000,0x3e00,0xbe000000,0x3e00,
0xbe000000,0x3e00,0xbdb5bdb5,0xbdb53db5,0xbcc83dfb,0x3dfb3cc8,0xbdd53d8e,0x3d8e3dd5,0x3ded3d44,0x3d44bded,0x3d443ded,0x3dedbd44,0x3d8ebdd5,0xbdd5bd8e,0x3dfbbcc8,0xbcc8bdfb,
0x8000be00,0xbe000000,0x3e000000,0xbe00,0xbdedbd44,0xbd443ded,0x3d44bded,0xbdedbd44,0xbdb53db5,0x3db53db5,0xbdb5bdb5,0xbdb53db5,0x3d443ded,0x3dedbd44,0xbded3d44,0x3d443ded,
0x3e000000,0xbe00,0xbdb53db5,0x3db53db5,0x3d8ebdd5,0xbdd5bd8e,0x3cc83dfb,0x3dfbbcc8,0xbd44bded,0xbded3d44,0x3ded3d44,0x3d44bded,0xbdfbbcc8,0xbcc83dfb,0x3dd5bd8e,0xbd8ebdd5,
0x80003e00,0x3e000000,0x8000be00,0xbe000000,0x3db53db5,0x3db5bdb5,0xbdb5bdb5,0xbdb53db5,0x3e000000,0xbe00,0xbe000000,0x3e00,0x3db5bdb5,0xbdb5bdb5,0xbdb53db5,0x3db53db5,
0xbe000000,0x3e00,0x3db53db5,0x3db5bdb5,0xbdd53d8e,0x3d8e3dd5,0x3dfb3cc8,0x3cc8bdfb,0xbd443ded,0x3ded3d44,0x3dedbd44,0xbd44bded,0x3cc83dfb,0x3dfbbcc8,0x3d8ebdd5,0xbdd5bd8e,
0x8000be00,0xbe000000,0xbe000000,0x3e00,0xbd44bded,0xbded3d44,0xbded3d44,0x3d443ded,0xbdb5bdb5,0xbdb53db5,0xbdb53db5,0x3db53db5,0xbdedbd44,0xbd443ded,0xbd443ded,0x3ded3d44,
0x3e000000,0xbe00,0x3db5bdb5,0xbdb5bdb5,0x3dfbbcc8,0xbcc8bdfb,0x3d8ebdd5,0xbdd5bd8e,0x3dedbd44,0xbd44bded,0x3d44bded,0xbdedbd44,0x3dd5bd8e,0xbd8ebdd5,0x3cc8bdfb,0xbdfbbcc8,
0x3e00,0xbe000000,0x3e00,0xbe000000,0x3e00,0xbe000000,0x3e00,0xbe000000,0x3e00,0xbe000000,0x3e00,0xbe000000,0x3e00,0xbe000000,0x3e00,0xbe000000,
0xbe00,0x3e000000,0xbdb5bdb5,0x3db5bdb5,0xbcc8bdfb,0x3dfbbcc8,0xbdd5bd8e,0x3d8ebdd5,0xbd44bded,0x3dedbd44,0xbdedbd44,0x3d44bded,0xbd8ebdd5,0x3dd5bd8e,0xbdfbbcc8,0x3cc8bdfb,
0x3e00,0xbe000000,0x3e000000,0x80003e00,0x3d443ded,0xbded3d44,0x3dedbd44,0x3d443ded,0x3db53db5,0xbdb53db5,0x3db5bdb5,0x3db53db5,0x3ded3d44,0xbd443ded,0x3d44bded,0x3ded3d44,
0xbe00,0x3e000000,0xbdb53db5,0xbdb5bdb5,0xbd8ebdd5,0x3dd5bd8e,0xbcc83dfb,0xbdfbbcc8,0xbdedbd44,0x3d44bded,0x3d443ded,0xbded3d44,0xbdfb3cc8,0xbcc8bdfb,0x3dd53d8e,0xbd8e3dd5,
0x3e00,0xbe000000,0xbe00,0x3e000000,0x3db53db5,0xbdb53db5,0xbdb5bdb5,0x3db5bdb5,0x3e000000,0x80003e00,0xbe000000,0x8000be00,0x3db5bdb5,0x3db53db5,0xbdb53db5,0xbdb5bdb5,
0xbe00,0x3e000000,0x3db53db5,0xbdb53db5,0xbdd5bd8e,0x3d8ebdd5,0x3dfbbcc8,0x3cc83dfb,0xbded3d44,0xbd44bded,0x3d44bded,0x3ded3d44,0xbcc83dfb,0xbdfbbcc8,0xbd8ebdd5,0x3dd5bd8e,
0x3e00,0xbe000000,0xbe000000,0x8000be00,0x3ded3d44,0xbd443ded,0xbd443ded,0xbdedbd44,0x3db5bdb5,0x3db53db5,0x3db53db5,0xbdb53db5,0xbd44bded,0x3dedbd44,0x3dedbd44,0x3d443ded,
0xbe00,0x3e000000,0x3db5bdb5,0x3db53db5,0xbdfbbcc8,0x3cc8bdfb,0xbd8ebdd5,0x3dd5bd8e,0xbd443ded,0xbdedbd44,0xbded3d44,0xbd44bded,0x3dd53d8e,0xbd8e3dd5,0x3cc83dfb,0xbdfb3cc8,
0x3e00,0xbe000000,0x3e00,0xbe000000,0x3e000000,0x80003e00,0x3e000000,0x80003e00,0xbe00,0x3e000000,0xbe00,0x3e000000,0xbe000000,0x8000be00,0xbe000000,0x8000be00,
0xbe00,0x3e000000,0xbdb5bdb5,0x3db5bdb5,0xbdfb3cc8,0xbcc8bdfb,0xbd8e3dd5,0xbdd5bd8e,0x3d443ded,0xbded3d44,0x3ded3d44,0xbd443ded,0x3dd5bd8e,0x3d8e3dd5,0x3cc8bdfb,0x3dfb3cc8,
0x3e00,0xbe000000,0x3e000000,0x80003e00,0x3dedbd44,0x3d443ded,0xbd44bded,0x3dedbd44,0xbdb5bdb5,0x3db5bdb5,0xbdb53db5,0xbdb5bdb5,0xbd443ded,0xbdedbd44,0x3ded3d44,0xbd443ded,
0xbe00,0x3e000000,0xbdb53db5,0xbdb5bdb5,0xbdd53d8e,0xbd8ebdd5,0x3dfb3cc8,0xbcc83dfb,0x3ded3d44,0xbd443ded,0xbd44bded,0x3dedbd44,0xbcc8bdfb,0x3dfbbcc8,0xbd8e3dd5,0xbdd5bd8e,
0x3e00,0xbe000000,0xbe00,0x3e000000,0x3db5bdb5,0x3db53db5,0xbdb53db5,0xbdb5bdb5,0xbe000000,0x8000be00,0x3e000000,0x80003e00,0x3db53db5,0xbdb53db5,0xbdb5bdb5,0x3db5bdb5,
0xbe00,0x3e000000,0x3db53db5,0xbdb53db5,0xbd8e3dd5,0xbdd5bd8e,0xbcc8bdfb,0x3dfbbcc8,0x3dedbd44,0x3d443ded,0xbd443ded,0xbdedbd44,0xbdfbbcc8,0x3cc8bdfb,0x3dd5bd8e,0x3d8e3dd5,
0x3e00,0xbe000000,0xbe000000,0x8000be00,0x3d44bded,0x3ded3d44,0x3ded3d44,0xbd443ded,0xbdb53db5,0xbdb5bdb5,0xbdb5bdb5,0x3db5bdb5,0x3dedbd44,0x3d443ded,0x3d443ded,0xbded3d44,
0xbe00,0x3e000000,0x3db5bdb5,0x3db53db5,0xbcc83dfb,0xbdfbbcc8,0xbdd53d8e,0xbd8ebdd5,0x3d44bded,0x3ded3d44,0x3dedbd44,0x3d443ded,0xbd8e3dd5,0xbdd5bd8e,0xbdfb3cc8,0xbcc8bdfb,
0x3e00,0xbe000000,0x3e00,0xbe000000,0xbe00,0x3e000000,0xbe00,0x3e000000,0x3e00,0xbe000000,0x3e00,0xbe000000,0xbe00,0x3e000000,0xbe00,0x3e000000,
0xbe00,0x3e000000,0xbdb5bdb5,0x3db5bdb5,0x3cc83dfb,0xbdfb3cc8,0x3dd53d8e,0xbd8e3dd5,0xbd44bded,0x3dedbd44,0xbdedbd44,0x3d44bded,0x3d8e3dd5,0xbdd53d8e,0x3dfb3cc8,0xbcc83dfb,
0x3e00,0xbe000000,0x3e000000,0x80003e00,0xbd44bded,0x3dedbd44,0xbded3d44,0xbd44bded,0x3db53db5,0xbdb53db5,0x3db5bdb5,0x3db53db5,0xbdedbd44,0x3d44bded,0xbd443ded,0xbdedbd44,
0xbe00,0x3e000000,0xbdb53db5,0xbdb5bdb5,0x3d8e3dd5,0xbdd53d8e,0x3cc8bdfb,0x3dfb3cc8,0xbdedbd44,0x3d44bded,0x3d443ded,0xbded3d44,0x3dfbbcc8,0x3cc83dfb,0xbdd5bd8e,0x3d8ebdd5,
0x3e00,0xbe000000,0xbe00,0x3e000000,0xbdb5bdb5,0x3db5bdb5,0x3db53db5,0xbdb53db5,0x3e000000,0x80003e00,0xbe000000,0x8000be00,0xbdb53db5,0xbdb5bdb5,0x3db5bdb5,0x3db53db5,
0xbe00,0x3e000000,0x3db53db5,0xbdb53db5,0x3dd53d8e,0xbd8e3dd5,0xbdfb3cc8,0xbcc8bdfb,0xbded3d44,0xbd44bded,0x3d44bded,0x3ded3d44,0x3cc8bdfb,0x3dfb3cc8,0x3d8e3dd5,0xbdd53d8e,
0x3e00,0xbe000000,0xbe000000,0x8000be00,0xbdedbd44,0x3d44bded,0x3d44bded,0x3ded3d44,0x3db5bdb5,0x3db53db5,0x3db53db5,0xbdb53db5,0x3d443ded,0xbded3d44,0xbded3d44,0xbd44bded,
0xbe00,0x3e000000,0x3db5bdb5,0x3db53db5,0x3dfb3cc8,0xbcc83dfb,0x3d8e3dd5,0xbdd53d8e,0xbd443ded,0xbdedbd44,0xbded3d44,0xbd44bded,0xbdd5bd8e,0x3d8ebdd5,0xbcc8bdfb,0x3dfbbcc8,
0x3e00,0xbe000000,0x3e00,0xbe000000,0xbe000000,0x8000be00,0xbe000000,0x8000be00,0xbe00,0x3e000000,0xbe00,0x3e000000,0x3e000000,0x80003e00,0x3e000000,0x80003e00,
0xbe00,0x3e000000,0xbdb5bdb5,0x3db5bdb5,0x3dfbbcc8,0x3cc83dfb,0x3d8ebdd5,0x3dd53d8e,0x3d443ded,0xbded3d44,0x3ded3d44,0xbd443ded,0xbdd53d8e,0xbd8ebdd5,0xbcc83dfb,0xbdfbbcc8,
0x3e00,0xbe000000,0x3e000000,0x80003e00,0xbded3d44,0xbd44bded,0x3d443ded,0xbded3d44,0xbdb5bdb5,0x3db5bdb5,0xbdb53db5,0xbdb5bdb5,0x3d44bded,0x3ded3d44,0xbdedbd44,0x3d44bded,
0xbe00,0x3e000000,0xbdb53db5,0xbdb5bdb5,0x3dd5bd8e,0x3d8e3dd5,0xbdfbbcc8,0x3cc8bdfb,0x3ded3d44,0xbd443ded,0xbd44bded,0x3dedbd44,0x3cc83dfb,0xbdfb3cc8,0x3d8ebdd5,0x3dd53d8e,
0x3e00,0xbe000000,0xbe00,0x3e000000,0xbdb53db5,0xbdb5bdb5,0x3db5bdb5,0x3db53db5,0xbe000000,0x8000be00,0x3e000000,0x80003e00,0xbdb5bdb5,0x3db5bdb5,0x3db53db5,0xbdb53db5,
0xbe00,0x3e000000,0x3db53db5,0xbdb53db5,0x3d8ebdd5,0x3dd53d8e,0x3cc83dfb,0xbdfb3cc8,0x3dedbd44,0x3d443ded,0xbd443ded,0xbdedbd44,0x3dfb3cc8,0xbcc83dfb,0xbdd53d8e,0xbd8ebdd5,
0x3e00,0xbe000000,0xbe000000,0x8000be00,0xbd443ded,0xbdedbd44,0xbdedbd44,0x3d44bded,0xbdb53db5,0xbdb5bdb5,0xbdb5bdb5,0x3db5bdb5,0xbded3d44,0xbd44bded,0xbd44bded,0x3dedbd44,
0xbe00,0x3e000000,0x3db5bdb5,0x3db53db5,0x3cc8bdfb,0x3dfb3cc8,0x3dd5bd8e,0x3d8e3dd5,0x3d44bded,0x3ded3d44,0x3dedbd44,0x3d443ded,0x3d8ebdd5,0x3dd53d8e,0x3dfbbcc8,0x3cc83dfb,
0x3e00,0xbe000000,0x3e00,0xbe000000,0x3e00,0xbe000000,0x3e00,0xbe000000,0x3e00,0xbe000000,0x3e00,0xbe000000,0x3e00,0xbe000000,0x3e00,0xbe000000,
0xbe000000,0x8000be00,0xbdb53db5,0xbdb5bdb5,0xbdfb3cc8,0xbcc8bdfb,0xbd8e3dd5,0xbdd5bd8e,0xbded3d44,0xbd44bded,0xbd443ded,0xbdedbd44,0xbdd53d8e,0xbd8ebdd5,0xbcc83dfb,0xbdfbbcc8,
0xbe00,0x3e000000,0xbe000000,0x8000be00,0xbd44bded,0x3dedbd44,0xbded3d44,0xbd44bded,0xbdb5bdb5,0x3db5bdb5,0xbdb53db5,0xbdb5bdb5,0xbdedbd44,0x3d44bded,0xbd443ded,0xbdedbd44,
0x3e000000,0x80003e00,0xbdb5bdb5,0x3db5bdb5,0x3dd5bd8e,0x3d8e3dd5,0xbdfbbcc8,0x3cc8bdfb,0x3d44bded,0x3ded3d44,0xbded3d44,0xbd44bded,0xbcc8bdfb,0x3dfbbcc8,0xbd8e3dd5,0xbdd5bd8e,
0x3e00,0xbe000000,0xbe00,0x3e000000,0x3db53db5,0xbdb53db5,0xbdb5bdb5,0x3db5bdb5,0x3e000000,0x80003e00,0xbe000000,0x8000be00,0x3db5bdb5,0x3db53db5,0xbdb53db5,0xbdb5bdb5,
0xbe000000,0x8000be00,0x3db5bdb5,0x3db53db5,0xbd8e3dd5,0xbdd5bd8e,0xbcc8bdfb,0x3dfbbcc8,0x3d443ded,0xbded3d44,0xbdedbd44,0x3d44bded,0x3dfb3cc8,0xbcc83dfb,0xbdd53d8e,0xbd8ebdd5,
0xbe00,0x3e000000,0x3e000000,0x80003e00,0xbdedbd44,0x3d44bded,0x3d44bded,0x3ded3d44,0xbdb53db5,0xbdb5bdb5,0xbdb5bdb5,0x3db5bdb5,0x3d443ded,0xbded3d44,0xbded3d44,0xbd44bded,
0x3e000000,0x80003e00,0x3db53db5,0xbdb53db5,0x3cc8bdfb,0x3dfb3cc8,0x3dd5bd8e,0x3d8e3dd5,0xbdedbd44,0x3d44bded,0xbd44bded,0x3dedbd44,0xbd8e3dd5,0xbdd5bd8e,0xbdfb3cc8,0xbcc8bdfb,
0x3e00,0xbe000000,0x3e00,0xbe000000,0x3e000000,0x80003e00,0x3e000000,0x80003e00,0xbe00,0x3e000000,0xbe00,0x3e000000,0xbe000000,0x8000be00,0xbe000000,0x8000be00,
0xbe000000,0x8000be00,0xbdb53db5,0xbdb5bdb5,0x3cc83dfb,0xbdfb3cc8,0x3dd53d8e,0xbd8e3dd5,0x3dedbd44,0x3d443ded,0x3d44bded,0x3ded3d44,0xbd8ebdd5,0x3dd5bd8e,0xbdfbbcc8,0x3cc8bdfb,
0xbe00,0x3e000000,0xbe000000,0x8000be00,0xbded3d44,0xbd44bded,0x3d443ded,0xbded3d44,0x3db53db5,0xbdb53db5,0x3db5bdb5,0x3db53db5,0x3d44bded,0x3ded3d44,0xbdedbd44,0x3d44bded,
0x3e000000,0x80003e00,0xbdb5bdb5,0x3db5bdb5,0xbd8ebdd5,0x3dd5bd8e,0xbcc83dfb,0xbdfbbcc8,0xbd443ded,0xbdedbd44,0x3dedbd44,0x3d443ded,0x3dfbbcc8,0x3cc83dfb,0xbdd5bd8e,0x3d8ebdd5,
0x3e00,0xbe000000,0xbe00,0x3e000000,0x3db5bdb5,0x3db53db5,0xbdb53db5,0xbdb5bdb5,0xbe000000,0x8000be00,0x3e000000,0x80003e00,0x3db53db5,0xbdb53db5,0xbdb5bdb5,0x3db5bdb5,
0xbe000000,0x8000be00,0x3db5bdb5,0x3db53db5,0x3dd53d8e,0xbd8e3dd5,0xbdfb3cc8,0xbcc8bdfb,0xbd44bded,0x3dedbd44,0x3ded3d44,0xbd443ded,0xbcc83dfb,0xbdfbbcc8,0xbd8ebdd5,0x3dd5bd8e,
0xbe00,0x3e000000,0x3e000000,0x80003e00,0xbd443ded,0xbdedbd44,0xbdedbd44,0x3d44bded,0x3db5bdb5,0x3db53db5,0x3db53db5,0xbdb53db5,0xbded3d44,0xbd44bded,0xbd44bded,0x3dedbd44,
0x3e000000,0x80003e00,0x3db53db5,0xbdb53db5,0xbdfbbcc8,0x3cc8bdfb,0xbd8ebdd5,0x3dd5bd8e,0x3ded3d44,0xbd443ded,0x3d443ded,0xbded3d44,0xbdd5bd8e,0x3d8ebdd5,0xbcc8bdfb,0x3dfbbcc8,
0x3e00,0xbe000000,0x3e00,0xbe000000,0xbe00,0x3e000000,0xbe00,0x3e000000,0x3e00,0xbe000000,0x3e00,0xbe000000,0xbe00,0x3e000000,0xbe00,0x3e000000,
0xbe000000,0x8000be00,0xbdb53db5,0xbdb5bdb5,0x3dfbbcc8,0x3cc83dfb,0x3d8ebdd5,0x3dd53d8e,0xbded3d44,0xbd44bded,0xbd443ded,0xbdedbd44,0x3dd5bd8e,0x3d8e3dd5,0x3cc8bdfb,0x3dfb3cc8,
0xbe00,0x3e000000,0xbe000000,0x8000be00,0x3d443ded,0xbded3d44,0x3dedbd44,0x3d443ded,0xbdb5bdb5,0x3db5bdb5,0xbdb53db5,0xbdb5bdb5,0x3ded3d44,0xbd443ded,0x3d44bded,0x3ded3d44,
0x3e000000,0x80003e00,0xbdb5bdb5,0x3db5bdb5,0xbdd53d8e,0xbd8ebdd5,0x3dfb3cc8,0xbcc83dfb,0x3d44bded,0x3ded3d44,0xbded3d44,0xbd44bded,0x3cc83dfb,0xbdfb3cc8,0x3d8ebdd5,0x3dd53d8e,
0x3e00,0xbe000000,0xbe00,0x3e000000,0xbdb5bdb5,0x3db5bdb5,0x3db53db5,0xbdb53db5,0x3e000000,0x80003e00,0xbe000000,0x8000be00,0xbdb53db5,0xbdb5bdb5,0x3db5bdb5,0x3db53db5,
0xbe000000,0x8000be00,0x3db5bdb5,0x3db53db5,0x3d8ebdd5,0x3dd53d8e,0x3cc83dfb,0xbdfb3cc8,0x3d443ded,0xbded3d44,0xbdedbd44,0x3d44bded,0xbdfbbcc8,0x3cc8bdfb,0x3dd5bd8e,0x3d8e3dd5,
0xbe00,0x3e000000,0x3e000000,0x80003e00,0x3ded3d44,0xbd443ded,0xbd443ded,0xbdedbd44,0xbdb53db5,0xbdb5bdb5,0xbdb5bdb5,0x3db5bdb5,0xbd44bded,0x3dedbd44,0x3dedbd44,0x3d443ded,
0x3e000000,0x80003e00,0x3db53db5,0xbdb53db5,0xbcc83dfb,0xbdfbbcc8,0xbdd53d8e,0xbd8ebdd5,0xbdedbd44,0x3d44bded,0xbd44bded,0x3dedbd44,0x3d8ebdd5,0x3dd53d8e,0x3dfbbcc8,0x3cc83dfb,
0x3e00,0xbe000000,0x3e00,0xbe000000,0xbe000000,0x8000be00,0xbe000000,0x8000be00,0xbe00,0x3e000000,0xbe00,0x3e000000,0x3e000000,0x80003e00,0x3e000000,0x80003e00,
0xbe000000,0x8000be00,0xbdb53db5,0xbdb5bdb5,0xbcc8bdfb,0x3dfbbcc8,0xbdd5bd8e,0x3d8ebdd5,0x3dedbd44,0x3d443ded,0x3d44bded,0x3ded3d44,0x3d8e3dd5,0xbdd53d8e,0x3dfb3cc8,0xbcc83dfb,
0xbe00,0x3e000000,0xbe000000,0x8000be00,0x3dedbd44,0x3d443ded,0xbd44bded,0x3dedbd44,0x3db53db5,0xbdb53db5,0x3db5bdb5,0x3db53db5,0xbd443ded,0xbdedbd44,0x3ded3d44,0xbd443ded,
0x3e000000,0x80003e00,0xbdb5bdb5,0x3db5bdb5,0x3d8e3dd5,0xbdd53d8e,0x3cc8bdfb,0x3dfb3cc8,0xbd443ded,0xbdedbd44,0x3dedbd44,0x3d443ded,0xbdfb3cc8,0xbcc8bdfb,0x3dd53d8e,0xbd8e3dd5,
0x3e00,0xbe000000,0xbe00,0x3e000000,0xbdb53db5,0xbdb5bdb5,0x3db5bdb5,0x3db53db5,0xbe000000,0x8000be00,0x3e000000,0x80003e00,0xbdb5bdb5,0x3db5bdb5,0x3db53db5,0xbdb53db5,
0xbe000000,0x8000be00,0x3db5bdb5,0x3db53db5,0xbdd5bd8e,0x3d8ebdd5,0x3dfbbcc8,0x3cc83dfb,0xbd44bded,0x3dedbd44,0x3ded3d44,0xbd443ded,0x3cc8bdfb,0x3dfb3cc8,0x3d8e3dd5,0xbdd53d8e,
0xbe00,0x3e000000,0x3e000000,0x80003e00,0x3d44bded,0x3ded3d44,0x3ded3d44,0xbd443ded,0x3db5bdb5,0x3db53db5,0x3db53db5,0xbdb53db5,0x3dedbd44,0x3d443ded,0x3d443ded,0xbded3d44,
0x3e000000,0x80003e00,0x3db53db5,0xbdb53db5,0x3dfb3cc8,0xbcc83dfb,0x3d8e3dd5,0xbdd53d8e,0x3ded3d44,0xbd443ded,0x3d443ded,0xbded3d44,0x3dd53d8e,0xbd8e3dd5,0x3cc83dfb,0xbdfb3cc8,
0x80003e00,0x3e000000,0x80003e00,0x3e000000,0x80003e00,0x3e000000,0x80003e00,0x3e000000,0x80003e00,0x3e000000,0x80003e00,0x3e000000,0x80003e00,0x3e000000,0x80003e00,0x3e000000,
0xbc493dff,0x3dff3c49,0xbdc63da2,0x3da23dc6,0xbd153df5,0x3df53d15,0xbde23d71,0x3d713de2,0xbd713de2,0x3de23d71,0xbdf53d15,0x3d153df5,0xbda23dc6,0x3dc63da2,0xbdff3c49,0x3c493dff,
0xbcc83dfb,0x3dfb3cc8,0xbdfbbcc8,0xbcc83dfb,0xbd8e3dd5,0x3dd53d8e,0xbdd5bd8e,0xbd8e3dd5,0xbdd53d8e,0x3d8e3dd5,0xbd8ebdd5,0xbdd53d8e,0xbdfb3cc8,0x3cc83dfb,0xbcc8bdfb,0xbdfb3cc8,
0xbd153df5,0x3df53d15,0xbd71bde2,0xbde23d71,0xbdc63da2,0x3da23dc6,0x3c49bdff,0xbdffbc49,0xbdff3c49,0x3c493dff,0x3da2bdc6,0xbdc6bda2,0xbde2bd71,0xbd713de2,0x3df5bd15,0xbd15bdf5,
0xbd443ded,0x3ded3d44,0x3d44bded,0xbdedbd44,0xbded3d44,0x3d443ded,0x3dedbd44,0xbd44bded,0xbdedbd44,0xbd443ded,0x3ded3d44,0x3d44bded,0xbd44bded,0xbded3d44,0x3d443ded,0x3dedbd44,
0xbd713de2,0x3de23d71,0x3df5bd15,0xbd15bdf5,0xbdff3c49,0x3c493dff,0x3dc63da2,0x3da2bdc6,0xbda2bdc6,0xbdc63da2,0xbc493dff,0x3dff3c49,0x3d15bdf5,0xbdf5bd15,0xbde23d71,0x3d713de2,
0xbd8e3dd5,0x3dd53d8e,0x3dd53d8e,0x3d8ebdd5,0xbdfbbcc8,0xbcc83dfb,0xbcc83dfb,0x3dfb3cc8,0xbcc8bdfb,0xbdfb3cc8,0xbdfb3cc8,0x3cc83dfb,0x3dd5bd8e,0xbd8ebdd5,0xbd8ebdd5,0xbdd53d8e,
0xbda23dc6,0x3dc63da2,0x3c493dff,0x3dffbc49,0xbde2bd71,0xbd713de2,0xbdf53d15,0x3d153df5,0x3d15bdf5,0xbdf5bd15,0xbd71bde2,0xbde23d71,0x3dff3c49,0x3c49bdff,0x3dc6bda2,0xbda2bdc6,
0xbdb53db5,0x3db53db5,0xbdb53db5,0x3db53db5,0xbdb5bdb5,0xbdb53db5,0xbdb5bdb5,0xbdb53db5,0x3db5bdb5,0xbdb5bdb5,0x3db5bdb5,0xbdb5bdb5,0x3db53db5,0x3db5bdb5,0x3db53db5,0x3db5bdb5,
0xbdc63da2,0x3da23dc6,0xbdffbc49,0xbc493dff,0xbd71bde2,0xbde23d71,0x3d15bdf5,0xbdf5bd15,0x3df5bd15,0xbd15bdf5,0x3de23d71,0x3d71bde2,0x3c493dff,0x3dffbc49,0xbda23dc6,0x3dc63da2,
0xbdd53d8e,0x3d8e3dd5,0xbd8ebdd5,0xbdd53d8e,0xbcc8bdfb,0xbdfb3cc8,0x3dfbbcc8,0xbcc8bdfb,0x3dfb3cc8,0x3cc8bdfb,0xbcc83dfb,0x3dfb3cc8,0xbd8e3dd5,0x3dd53d8e,0xbdd5bd8e,0xbd8e3dd5,
0xbde23d71,0x3d713de2,0x3d15bdf5,0xbdf5bd15,0x3c49bdff,0xbdffbc49,0x3da23dc6,0x3dc6bda2,0x3dc63da2,0x3da2bdc6,0xbdff3c49,0x3c493dff,0xbdf53d15,0x3d153df5,0x3d71bde2,0xbde2bd71,
0xbded3d44,0x3d443ded,0x3dedbd44,0xbd44bded,0x3d44bded,0xbdedbd44,0xbd443ded,0x3ded3d44,0x3d443ded,0x3dedbd44,0xbd44bded,0xbded3d44,0xbdedbd44,0xbd443ded,0x3ded3d44,0x3d44bded,
0xbdf53d15,0x3d153df5,0x3de23d71,0x3d71bde2,0x3da2bdc6,0xbdc6bda2,0xbdff3c49,0x3c493dff,0xbc493dff,0x3dff3c49,0x3dc6bda2,0xbda2bdc6,0xbd71bde2,0xbde23d71,0xbd153df5,0x3df53d15,
0xbdfb3cc8,0x3cc83dfb,0x3cc83dfb,0x3dfbbcc8,0x3dd5bd8e,0xbd8ebdd5,0xbd8ebdd5,0xbdd53d8e,0xbd8e3dd5,0x3dd53d8e,0x3dd53d8e,0x3d8ebdd5,0x3cc8bdfb,0xbdfbbcc8,0xbdfbbcc8,0xbcc83dfb,
0xbdff3c49,0x3c493dff,0xbda23dc6,0x3dc63da2,0x3df5bd15,0xbd15bdf5,0x3d71bde2,0xbde2bd71,0xbde23d71,0x3d713de2,0xbd153df5,0x3df53d15,0x3dc6bda2,0xbda2bdc6,0x3c49bdff,0xbdffbc49,
0xbe000000,0x3e00,0xbe000000,0x3e00,0x3e000000,0xbe00,0x3e000000,0xbe00,0xbe000000,0x3e00,0xbe000000,0x3e00,0x3e000000,0xbe00,0x3e000000,0xbe00,
0xbdffbc49,0xbc493dff,0xbda2bdc6,0xbdc63da2,0x3df53d15,0x3d15bdf5,0x3d713de2,0x3de2bd71,0xbde2bd71,0xbd713de2,0xbd15bdf5,0xbdf53d15,0x3dc63da2,0x3da2bdc6,0x3c493dff,0x3dffbc49,
0xbdfbbcc8,0xbcc83dfb,0x3cc8bdfb,0xbdfbbcc8,0x3dd53d8e,0x3d8ebdd5,0xbd8e3dd5,0x3dd53d8e,0xbd8ebdd5,0xbdd53d8e,0x3dd5bd8e,0xbd8ebdd5,0x3cc83dfb,0x3dfbbcc8,0xbdfb3cc8,0x3cc83dfb,
0xbdf5bd15,0xbd153df5,0x3de2bd71,0xbd71bde2,0x3da23dc6,0x3dc6bda2,0xbdffbc49,0xbc493dff,0xbc49bdff,0xbdff3c49,0x3dc63da2,0x3da2bdc6,0xbd713de2,0x3de23d71,0xbd15bdf5,0xbdf53d15,
0xbdedbd44,0xbd443ded,0x3ded3d44,0x3d44bded,0x3d443ded,0x3dedbd44,0xbd44bded,0xbded3d44,0x3d44bded,0xbdedbd44,0xbd443ded,0x3ded3d44,0xbded3d44,0x3d443ded,0x3dedbd44,0xbd44bded,
0xbde2bd71,0xbd713de2,0x3d153df5,0x3df5bd15,0x3c493dff,0x3dffbc49,0x3da2bdc6,0xbdc6bda2,0x3dc6bda2,0xbda2bdc6,0xbdffbc49,0xbc493dff,0xbdf5bd15,0xbd153df5,0x3d713de2,0x3de2bd71,
0xbdd5bd8e,0xbd8e3dd5,0xbd8e3dd5,0x3dd53d8e,0xbcc83dfb,0x3dfb3cc8,0x3dfb3cc8,0x3cc8bdfb,0x3dfbbcc8,0xbcc8bdfb,0xbcc8bdfb,0xbdfb3cc8,0xbd8ebdd5,0xbdd53d8e,0xbdd53d8e,0x3d8e3dd5,
0xbdc6bda2,0xbda23dc6,0xbdff3c49,0x3c493dff,0xbd713de2,0x3de23d71,0x3d153df5,0x3df5bd15,0x3df53d15,0x3d15bdf5,0x3de2bd71,0xbd71bde2,0x3c49bdff,0xbdffbc49,0xbda2bdc6,0xbdc63da2,
0xbdb5bdb5,0xbdb53db5,0xbdb5bdb5,0xbdb53db5,0xbdb53db5,0x3db53db5,0xbdb53db5,0x3db53db5,0x3db53db5,0x3db5bdb5,0x3db53db5,0x3db5bdb5,0x3db5bdb5,0xbdb5bdb5,0x3db5bdb5,0xbdb5bdb5,
0xbda2bdc6,0xbdc63da2,0x3c49bdff,0xbdffbc49,0xbde23d71,0x3d713de2,0xbdf5bd15,0xbd153df5,0x3d153df5,0x3df5bd15,0xbd713de2,0x3de23d71,0x3dffbc49,0xbc49bdff,0x3dc63da2,0x3da2bdc6,
0xbd8ebdd5,0xbdd53d8e,0x3dd5bd8e,0xbd8ebdd5,0xbdfb3cc8,0x3cc83dfb,0xbcc8bdfb,0xbdfb3cc8,0xbcc83dfb,0x3dfb3cc8,0xbdfbbcc8,0xbcc83dfb,0x3dd53d8e,0x3d8ebdd5,0xbd8e3dd5,0x3dd53d8e,
0xbd71bde2,0xbde23d71,0x3df53d15,0x3d15bdf5,0xbdffbc49,0xbc493dff,0x3dc6bda2,0xbda2bdc6,0xbda23dc6,0x3dc63da2,0xbc49bdff,0xbdff3c49,0x3d153df5,0x3df5bd15,0xbde2bd71,0xbd713de2,
0xbd44bded,0xbded3d44,0x3d443ded,0x3dedbd44,0xbdedbd44,0xbd443ded,0x3ded3d44,0x3d44bded,0xbded3d44,0x3d443ded,0x3dedbd44,0xbd44bded,0xbd443ded,0x3ded3d44,0x3d44bded,0xbdedbd44,
0xbd15bdf5,0xbdf53d15,0xbd713de2,0x3de23d71,0xbdc6bda2,0xbda23dc6,0x3c493dff,0x3dffbc49,0xbdffbc49,0xbc493dff,0x3da23dc6,0x3dc6bda2,0xbde23d71,0x3d713de2,0x3df53d15,0x3d15bdf5,
0xbcc8bdfb,0xbdfb3cc8,0xbdfb3cc8,0x3cc83dfb,0xbd8ebdd5,0xbdd53d8e,0xbdd53d8e,0x3d8e3dd5,0xbdd5bd8e,0xbd8e3dd5,0xbd8e3dd5,0x3dd53d8e,0xbdfbbcc8,0xbcc83dfb,0xbcc83dfb,0x3dfb3cc8,
0xbc49bdff,0xbdff3c49,0xbdc6bda2,0xbda23dc6,0xbd15bdf5,0xbdf53d15,0xbde2bd71,0xbd713de2,0xbd71bde2,0xbde23d71,0xbdf5bd15,0xbd153df5,0xbda2bdc6,0xbdc63da2,0xbdffbc49,0xbc493dff,
0x80003e00,0x3e000000,0x80003e00,0x3e000000,0x80003e00,0x3e000000,0x80003e00,0x3e000000,0x80003e00,0x3e000000,0x80003e00,0x3e000000,0x80003e00,0x3e000000,0x80003e00,0x3e000000,
0xbdffbc49,0xbc493dff,0xbda2bdc6,0xbdc63da2,0xbdf5bd15,0xbd153df5,0xbd71bde2,0xbde23d71,0xbde2bd71,0xbd713de2,0xbd15bdf5,0xbdf53d15,0xbdc6bda2,0xbda23dc6,0xbc49bdff,0xbdff3c49,
0x3cc8bdfb,0xbdfbbcc8,0x3dfb3cc8,0x3cc8bdfb,0x3d8ebdd5,0xbdd5bd8e,0x3dd53d8e,0x3d8ebdd5,0x3dd5bd8e,0xbd8ebdd5,0x3d8e3dd5,0x3dd5bd8e,0x3dfbbcc8,0xbcc8bdfb,0x3cc83dfb,0x3dfbbcc8,
0x3df53d15,0x3d15bdf5,0xbde23d71,0x3d713de2,0x3da23dc6,0x3dc6bda2,0xbdffbc49,0xbc493dff,0x3c493dff,0x3dffbc49,0xbdc6bda2,0xbda23dc6,0xbd713de2,0x3de23d71,0xbd15bdf5,0xbdf53d15,
0xbd443ded,0x3ded3d44,0x3d44bded,0xbdedbd44,0xbded3d44,0x3d443ded,0x3dedbd44,0xbd44bded,0xbdedbd44,0xbd443ded,0x3ded3d44,0x3d44bded,0xbd44bded,0xbded3d44,0x3d443ded,0x3dedbd44,
0xbde2bd71,0xbd713de2,0x3d153df5,0x3df5bd15,0xbc49bdff,0xbdff3c49,0xbda23dc6,0x3dc63da2,0x3dc6bda2,0xbda2bdc6,0xbdffbc49,0xbc493dff,0x3df53d15,0x3d15bdf5,0xbd71bde2,0xbde23d71,
0x3d8ebdd5,0xbdd5bd8e,0xbdd5bd8e,0xbd8e3dd5,0x3dfb3cc8,0x3cc8bdfb,0x3cc8bdfb,0xbdfbbcc8,0x3cc83dfb,0x3dfbbcc8,0x3dfbbcc8,0xbcc8bdfb,0xbdd53d8e,0x3d8e3dd5,0x3d8e3dd5,0x3dd5bd8e,
0x3dc63da2,0x3da2bdc6,0x3dffbc49,0xbc49bdff,0xbd713de2,0x3de23d71,0x3d153df5,0x3df5bd15,0xbdf5bd15,0xbd153df5,0xbde23d71,0x3d713de2,0x3c49bdff,0xbdffbc49,0xbda2bdc6,0xbdc63da2,
0xbdb53db5,0x3db53db5,0xbdb53db5,0x3db53db5,0xbdb5bdb5,0xbdb53db5,0xbdb5bdb5,0xbdb53db5,0x3db5bdb5,0xbdb5bdb5,0x3db5bdb5,0xbdb5bdb5,0x3db53db5,0x3db5bdb5,0x3db53db5,0x3db5bdb5,
0xbda2bdc6,0xbdc63da2,0x3c49bdff,0xbdffbc49,0x3de2bd71,0xbd71bde2,0x3df53d15,0x3d15bdf5,0x3d153df5,0x3df5bd15,0xbd713de2,0x3de23d71,0xbdff3c49,0x3c493dff,0xbdc6bda2,0xbda23dc6,
0x3dd5bd8e,0xbd8ebdd5,0x3d8e3dd5,0x3dd5bd8e,0x3cc83dfb,0x3dfbbcc8,0xbdfb3cc8,0x3cc83dfb,0xbdfbbcc8,0xbcc83dfb,0x3cc8bdfb,0xbdfbbcc8,0x3d8ebdd5,0xbdd5bd8e,0x3dd53d8e,0x3d8ebdd5,
0x3d713de2,0x3de2bd71,0xbdf5bd15,0xbd153df5,0xbdffbc49,0xbc493dff,0x3dc6bda2,0xbda2bdc6,0x3da2bdc6,0xbdc6bda2,0x3c493dff,0x3dffbc49,0x3d153df5,0x3df5bd15,0xbde2bd71,0xbd713de2,
0xbded3d44,0x3d443ded,0x3dedbd44,0xbd44bded,0x3d44bded,0xbdedbd44,0xbd443ded,0x3ded3d44,0x3d443ded,0x3dedbd44,0xbd44bded,0xbded3d44,0xbdedbd44,0xbd443ded,0x3ded3d44,0x3d44bded,
0xbd15bdf5,0xbdf53d15,0xbd713de2,0x3de23d71,0x3dc63da2,0x3da2bdc6,0xbc49bdff,0xbdff3c49,0xbdffbc49,0xbc493dff,0x3da23dc6,0x3dc6bda2,0x3de2bd71,0xbd71bde2,0xbdf5bd15,0xbd153df5,
0x3dfbbcc8,0xbcc8bdfb,0xbcc8bdfb,0xbdfb3cc8,0xbdd53d8e,0x3d8e3dd5,0x3d8e3dd5,0x3dd5bd8e,0x3d8ebdd5,0xbdd5bd8e,0xbdd5bd8e,0xbd8e3dd5,0xbcc83dfb,0x3dfb3cc8,0x3dfb3cc8,0x3cc8bdfb,
0x3c493dff,0x3dffbc49,0x3dc63da2,0x3da2bdc6,0xbd15bdf5,0xbdf53d15,0xbde2bd71,0xbd713de2,0x3d713de2,0x3de2bd71,0x3df53d15,0x3d15bdf5,0xbda2bdc6,0xbdc63da2,0xbdffbc49,0xbc493dff,
0xbe000000,0x3e00,0xbe000000,0x3e00,0x3e000000,0xbe00,0x3e000000,0xbe00,0xbe000000,0x3e00,0xbe000000,0x3e00,0x3e000000,0xbe00,0x3e000000,0xbe00,
0x3c49bdff,0xbdffbc49,0x3dc6bda2,0xbda2bdc6,0xbd153df5,0x3df53d15,0xbde23d71,0x3d713de2,0x3d71bde2,0xbde2bd71,0x3df5bd15,0xbd15bdf5,0xbda23dc6,0x3dc63da2,0xbdff3c49,0x3c493dff,
0x3dfb3cc8,0x3cc8bdfb,0xbcc83dfb,0x3dfb3cc8,0xbdd5bd8e,0xbd8e3dd5,0x3d8ebdd5,0xbdd5bd8e,0x3d8e3dd5,0x3dd5bd8e,0xbdd53d8e,0x3d8e3dd5,0xbcc8bdfb,0xbdfb3cc8,0x3dfbbcc8,0xbcc8bdfb,
0xbd153df5,0x3df53d15,0xbd71bde2,0xbde23d71,0x3dc6bda2,0xbda2bdc6,0xbc493dff,0x3dff3c49,0xbdff3c49,0x3c493dff,0x3da2bdc6,0xbdc6bda2,0x3de23d71,0x3d71bde2,0xbdf53d15,0x3d153df5,
0xbdedbd44,0xbd443ded,0x3ded3d44,0x3d44bded,0x3d443ded,0x3dedbd44,0xbd44bded,0xbded3d44,0x3d44bded,0xbdedbd44,0xbd443ded,0x3ded3d44,0xbded3d44,0x3d443ded,0x3dedbd44,0xbd44bded,
0x3d71bde2,0xbde2bd71,0xbdf53d15,0x3d153df5,0xbdff3c49,0x3c493dff,0x3dc63da2,0x3da2bdc6,0x3da23dc6,0x3dc6bda2,0x3c49bdff,0xbdffbc49,0x3d15bdf5,0xbdf5bd15,0xbde23d71,0x3d713de2,
0x3dd53d8e,0x3d8ebdd5,0x3d8ebdd5,0xbdd5bd8e,0x3cc8bdfb,0xbdfbbcc8,0xbdfbbcc8,0xbcc83dfb,0xbdfb3cc8,0x3cc83dfb,0x3cc83dfb,0x3dfbbcc8,0x3d8e3dd5,0x3dd5bd8e,0x3dd5bd8e,0xbd8ebdd5,
0xbda23dc6,0x3dc63da2,0x3c493dff,0x3dffbc49,0x3de23d71,0x3d71bde2,0x3df5bd15,0xbd15bdf5,0x3d15bdf5,0xbdf5bd15,0xbd71bde2,0xbde23d71,0xbdffbc49,0xbc493dff,0xbdc63da2,0x3da23dc6,
0xbdb5bdb5,0xbdb53db5,0xbdb5bdb5,0xbdb53db5,0xbdb53db5,0x3db53db5,0xbdb53db5,0x3db53db5,0x3db53db5,0x3db5bdb5,0x3db53db5,0x3db5bdb5,0x3db5bdb5,0xbdb5bdb5,0x3db5bdb5,0xbdb5bdb5,
0x3dc6bda2,0xbda2bdc6,0x3dff3c49,0x3c49bdff,0xbd71bde2,0xbde23d71,0x3d15bdf5,0xbdf5bd15,0xbdf53d15,0x3d153df5,0xbde2bd71,0xbd713de2,0x3c493dff,0x3dffbc49,0xbda23dc6,0x3dc63da2,
0x3d8e3dd5,0x3dd5bd8e,0xbdd53d8e,0x3d8e3dd5,0x3dfbbcc8,0xbcc8bdfb,0x3cc83dfb,0x3dfbbcc8,0x3cc8bdfb,0xbdfbbcc8,0x3dfb3cc8,0x3cc8bdfb,0xbdd5bd8e,0xbd8e3dd5,0x3d8ebdd5,0xbdd5bd8e,
0xbde23d71,0x3d713de2,0x3d15bdf5,0xbdf5bd15,0xbc493dff,0x3dff3c49,0xbda2bdc6,0xbdc63da2,0x3dc63da2,0x3da2bdc6,0xbdff3c49,0x3c493dff,0x3df5bd15,0xbd15bdf5,0xbd713de2,0x3de23d71,
0xbd44bded,0xbded3d44,0x3d443ded,0x3dedbd44,0xbdedbd44,0xbd443ded,0x3ded3d44,0x3d44bded,0xbded3d44,0x3d443ded,0x3dedbd44,0xbd44bded,0xbd443ded,0x3ded3d44,0x3d44bded,0xbdedbd44,
0x3df5bd15,0xbd15bdf5,0xbde2bd71,0xbd713de2,0x3da2bdc6,0xbdc6bda2,0xbdff3c49,0x3c493dff,0x3c49bdff,0xbdffbc49,0xbdc63da2,0x3da23dc6,0xbd71bde2,0xbde23d71,0xbd153df5,0x3df53d15,
0x3cc83dfb,0x3dfbbcc8,0x3dfbbcc8,0xbcc8bdfb,0x3d8e3dd5,0x3dd5bd8e,0x3dd5bd8e,0xbd8ebdd5,0x3dd53d8e,0x3d8ebdd5,0x3d8ebdd5,0xbdd5bd8e,0x3dfb3cc8,0x3cc8bdfb,0x3cc8bdfb,0xbdfbbcc8,
0xbdff3c49,0x3c493dff,0xbda23dc6,0x3dc63da2,0xbdf53d15,0x3d153df5,0xbd713de2,0x3de23d71,0xbde23d71,0x3d713de2,0xbd153df5,0x3df53d15,0xbdc63da2,0x3da23dc6,0xbc493dff,0x3dff3c49,
0x3e00,0xbe000000,0x3e00,0xbe000000,0x3e00,0xbe000000,0x3e00,0xbe000000,0x3e00,0xbe000000,0x3e00,0xbe000000,0x3e00,0xbe000000,0x3e00,0xbe000000,
0xbc49bdff,0x3dffbc49,0xbdc6bda2,0x3da2bdc6,0xbd15bdf5,0x3df5bd15,0xbde2bd71,0x3d71bde2,0xbd71bde2,0x3de2bd71,0xbdf5bd15,0x3d15bdf5,0xbda2bdc6,0x3dc6bda2,0xbdffbc49,0x3c49bdff,
0x3cc83dfb,0xbdfb3cc8,0x3dfbbcc8,0x3cc83dfb,0x3d8e3dd5,0xbdd53d8e,0x3dd5bd8e,0x3d8e3dd5,0x3dd53d8e,0xbd8e3dd5,0x3d8ebdd5,0x3dd53d8e,0x3dfb3cc8,0xbcc83dfb,0x3cc8bdfb,0x3dfb3cc8,
0xbd15bdf5,0x3df5bd15,0xbd713de2,0xbde2bd71,0xbdc6bda2,0x3da2bdc6,0x3c493dff,0xbdff3c49,0xbdffbc49,0x3c49bdff,0x3da23dc6,0xbdc63da2,0xbde23d71,0xbd71bde2,0x3df53d15,0xbd153df5,
0x3d443ded,0xbded3d44,0xbd44bded,0x3dedbd44,0x3ded3d44,0xbd443ded,0xbdedbd44,0x3d44bded,0x3dedbd44,0x3d443ded,0xbded3d44,0xbd44bded,0x3d44bded,0x3ded3d44,0xbd443ded,0xbdedbd44,
0xbd71bde2,0x3de2bd71,0x3df53d15,0xbd153df5,0xbdffbc49,0x3c49bdff,0x3dc6bda2,0x3da23dc6,0xbda23dc6,0xbdc6bda2,0xbc49bdff,0x3dffbc49,0x3d153df5,0xbdf53d15,0xbde2bd71,0x3d71bde2,
0x3d8e3dd5,0xbdd53d8e,0xbdd53d8e,0xbd8ebdd5,0x3dfbbcc8,0x3cc83dfb,0x3cc83dfb,0xbdfb3cc8,0x3cc8bdfb,0x3dfb3cc8,0x3dfb3cc8,0xbcc83dfb,0xbdd5bd8e,0x3d8ebdd5,0x3d8ebdd5,0x3dd53d8e,
0xbda2bdc6,0x3dc6bda2,0x3c49bdff,0x3dff3c49,0xbde23d71,0xbd71bde2,0xbdf5bd15,0x3d15bdf5,0x3d153df5,0xbdf53d15,0xbd713de2,0xbde2bd71,0x3dffbc49,0x3c493dff,0x3dc63da2,0xbda23dc6,
0x3db53db5,0xbdb53db5,0x3db53db5,0xbdb53db5,0x3db5bdb5,0x3db53db5,0x3db5bdb5,0x3db53db5,0xbdb5bdb5,0x3db5bdb5,0xbdb5bdb5,0x3db5bdb5,0xbdb53db5,0xbdb5bdb5,0xbdb53db5,0xbdb5bdb5,
0xbdc6bda2,0x3da2bdc6,0xbdff3c49,0xbc49bdff,0xbd713de2,0xbde2bd71,0x3d153df5,0xbdf53d15,0x3df53d15,0xbd153df5,0x3de2bd71,0x3d713de2,0x3c49bdff,0x3dff3c49,0xbda2bdc6,0x3dc6bda2,
0x3dd53d8e,0xbd8e3dd5,0x3d8ebdd5,0x3dd53d8e,0x3cc8bdfb,0x3dfb3cc8,0xbdfbbcc8,0x3cc8bdfb,0xbdfb3cc8,0xbcc8bdfb,0x3cc83dfb,0xbdfb3cc8,0x3d8e3dd5,0xbdd53d8e,0x3dd5bd8e,0x3d8e3dd5,
0xbde2bd71,0x3d71bde2,0x3d153df5,0xbdf53d15,0x3c493dff,0xbdff3c49,0x3da2bdc6,0x3dc63da2,0x3dc6bda2,0x3da23dc6,0xbdffbc49,0x3c49bdff,0xbdf5bd15,0x3d15bdf5,0x3d713de2,0xbde23d71,
0x3ded3d44,0xbd443ded,0xbdedbd44,0x3d44bded,0xbd44bded,0x3dedbd44,0x3d443ded,0xbded3d44,0xbd443ded,0xbdedbd44,0x3d44bded,0x3ded3d44,0x3dedbd44,0x3d443ded,0xbded3d44,0xbd44bded,
0xbdf5bd15,0x3d15bdf5,0x3de2bd71,0x3d713de2,0x3da23dc6,0xbdc63da2,0xbdffbc49,0x3c49bdff,0xbc49bdff,0x3dffbc49,0x3dc63da2,0xbda23dc6,0xbd713de2,0xbde2bd71,0xbd15bdf5,0x3df5bd15,
0x3dfb3cc8,0xbcc83dfb,0xbcc83dfb,0xbdfbbcc8,0xbdd5bd8e,0x3d8ebdd5,0x3d8ebdd5,0x3dd53d8e,0x3d8e3dd5,0xbdd53d8e,0xbdd53d8e,0xbd8ebdd5,0xbcc8bdfb,0x3dfbbcc8,0x3dfbbcc8,0x3cc83dfb,
0xbdffbc49,0x3c49bdff,0xbda2bdc6,0x3dc6bda2,0x3df53d15,0xbd153df5,0x3d713de2,0xbde23d71,0xbde2bd71,0x3d71bde2,0xbd15bdf5,0x3df5bd15,0x3dc63da2,0xbda23dc6,0x3c493dff,0xbdff3c49,
0x3e000000,0x80003e00,0x3e000000,0x80003e00,0xbe000000,0x8000be00,0xbe000000,0x8000be00,0x3e000000,0x80003e00,0x3e000000,0x80003e00,0xbe000000,0x8000be00,0xbe000000,0x8000be00,
0xbdff3c49,0xbc49bdff,0xbda23dc6,0xbdc6bda2,0x3df5bd15,0x3d153df5,0x3d71bde2,0x3de23d71,0xbde23d71,0xbd71bde2,0xbd153df5,0xbdf5bd15,0x3dc6bda2,0x3da23dc6,0x3c49bdff,0x3dff3c49,
0x3dfbbcc8,0x3cc83dfb,0xbcc8bdfb,0x3dfbbcc8,0xbdd53d8e,0xbd8ebdd5,0x3d8e3dd5,0xbdd53d8e,0x3d8ebdd5,0x3dd53d8e,0xbdd5bd8e,0x3d8ebdd5,0xbcc83dfb,0xbdfbbcc8,0x3dfb3cc8,0xbcc83dfb,
0xbdf53d15,0xbd15bdf5,0x3de23d71,0xbd713de2,0x3da2bdc6,0x3dc63da2,0xbdff3c49,0xbc49bdff,0xbc493dff,0xbdffbc49,0x3dc6bda2,0x3da23dc6,0xbd71bde2,0x3de2bd71,0xbd153df5,0xbdf5bd15,
0x3dedbd44,0x3d443ded,0xbded3d44,0xbd44bded,0xbd443ded,0xbdedbd44,0x3d44bded,0x3ded3d44,0xbd44bded,0x3dedbd44,0x3d443ded,0xbded3d44,0x3ded3d44,0xbd443ded,0xbdedbd44,0x3d44bded,
0xbde23d71,0xbd71bde2,0x3d15bdf5,0x3df53d15,0x3c49bdff,0x3dff3c49,0x3da23dc6,0xbdc63da2,0x3dc63da2,0xbda23dc6,0xbdff3c49,0xbc49bdff,0xbdf53d15,0xbd15bdf5,0x3d71bde2,0x3de23d71,
0x3dd5bd8e,0x3d8e3dd5,0x3d8e3dd5,0xbdd53d8e,0x3cc83dfb,0xbdfb3cc8,0xbdfb3cc8,0xbcc8bdfb,0xbdfbbcc8,0x3cc8bdfb,0x3cc8bdfb,0x3dfb3cc8,0x3d8ebdd5,0x3dd53d8e,0x3dd53d8e,0xbd8e3dd5,
0xbdc63da2,0xbda2bdc6,0xbdffbc49,0x3c49bdff,0xbd71bde2,0x3de2bd71,0x3d15bdf5,0x3df53d15,0x3df5bd15,0x3d153df5,0x3de23d71,0xbd713de2,0x3c493dff,0xbdff3c49,0xbda23dc6,0xbdc6bda2,
0x3db5bdb5,0x3db53db5,0x3db5bdb5,0x3db53db5,0x3db53db5,0xbdb53db5,0x3db53db5,0xbdb53db5,0xbdb53db5,0xbdb5bdb5,0xbdb53db5,0xbdb5bdb5,0xbdb5bdb5,0x3db5bdb5,0xbdb5bdb5,0x3db5bdb5,
0xbda23dc6,0xbdc6bda2,0x3c493dff,0xbdff3c49,0xbde2bd71,0x3d71bde2,0xbdf53d15,0xbd15bdf5,0x3d15bdf5,0x3df53d15,0xbd71bde2,0x3de2bd71,0x3dff3c49,0xbc493dff,0x3dc6bda2,0x3da23dc6,
0x3d8ebdd5,0x3dd53d8e,0xbdd5bd8e,0x3d8ebdd5,0x3dfb3cc8,0xbcc83dfb,0x3cc8bdfb,0x3dfb3cc8,0x3cc83dfb,0xbdfb3cc8,0x3dfbbcc8,0x3cc83dfb,0xbdd53d8e,0xbd8ebdd5,0x3d8e3dd5,0xbdd53d8e,
0xbd713de2,0xbde2bd71,0x3df5bd15,0x3d153df5,0xbdff3c49,0xbc49bdff,0x3dc63da2,0xbda23dc6,0xbda2bdc6,0x3dc6bda2,0xbc493dff,0xbdffbc49,0x3d15bdf5,0x3df53d15,0xbde23d71,0xbd71bde2,
0x3d44bded,0x3ded3d44,0xbd443ded,0xbdedbd44,0x3dedbd44,0x3d443ded,0xbded3d44,0xbd44bded,0x3ded3d44,0xbd443ded,0xbdedbd44,0x3d44bded,0x3d443ded,0xbded3d44,0xbd44bded,0x3dedbd44,
0xbd153df5,0xbdf5bd15,0xbd71bde2,0x3de2bd71,0xbdc63da2,0xbda2bdc6,0x3c49bdff,0x3dff3c49,0xbdff3c49,0xbc49bdff,0x3da2bdc6,0x3dc63da2,0xbde2bd71,0x3d71bde2,0x3df5bd15,0x3d153df5,
0x3cc8bdfb,0x3dfb3cc8,0x3dfb3cc8,0xbcc83dfb,0x3d8ebdd5,0x3dd53d8e,0x3dd53d8e,0xbd8e3dd5,0x3dd5bd8e,0x3d8e3dd5,0x3d8e3dd5,0xbdd53d8e,0x3dfbbcc8,0x3cc83dfb,0x3cc83dfb,0xbdfb3cc8,
0xbc493dff,0xbdffbc49,0xbdc63da2,0xbda2bdc6,0xbd153df5,0xbdf5bd15,0xbde23d71,0xbd71bde2,0xbd713de2,0xbde2bd71,0xbdf53d15,0xbd15bdf5,0xbda23dc6,0xbdc6bda2,0xbdff3c49,0xbc49bdff,
0x3e00,0xbe000000,0x3e00,0xbe000000,0x3e00,0xbe000000,0x3e00,0xbe000000,0x3e00,0xbe000000,0x3e00,0xbe000000,0x3e00,0xbe000000,0x3e00,0xbe000000,
0xbdff3c49,0xbc49bdff,0xbda23dc6,0xbdc6bda2,0xbdf53d15,0xbd15bdf5,0xbd713de2,0xbde2bd71,0xbde23d71,0xbd71bde2,0xbd153df5,0xbdf5bd15,0xbdc63da2,0xbda2bdc6,0xbc493dff,0xbdffbc49,
0xbcc8bdfb,0x3dfbbcc8,0xbdfb3cc8,0xbcc8bdfb,0xbd8ebdd5,0x3dd5bd8e,0xbdd53d8e,0xbd8ebdd5,0xbdd5bd8e,0x3d8ebdd5,0xbd8e3dd5,0xbdd5bd8e,0xbdfbbcc8,0x3cc8bdfb,0xbcc83dfb,0xbdfbbcc8,
0x3df5bd15,0x3d153df5,0xbde2bd71,0x3d71bde2,0x3da2bdc6,0x3dc63da2,0xbdff3c49,0xbc49bdff,0x3c49bdff,0x3dff3c49,0xbdc63da2,0xbda2bdc6,0xbd71bde2,0x3de2bd71,0xbd153df5,0xbdf5bd15,
0x3d443ded,0xbded3d44,0xbd44bded,0x3dedbd44,0x3ded3d44,0xbd443ded,0xbdedbd44,0x3d44bded,0x3dedbd44,0x3d443ded,0xbded3d44,0xbd44bded,0x3d44bded,0x3ded3d44,0xbd443ded,0xbdedbd44,
0xbde23d71,0xbd71bde2,0x3d15bdf5,0x3df53d15,0xbc493dff,0xbdffbc49,0xbda2bdc6,0x3dc6bda2,0x3dc63da2,0xbda23dc6,0xbdff3c49,0xbc49bdff,0x3df5bd15,0x3d153df5,0xbd713de2,0xbde2bd71,
0xbd8ebdd5,0x3dd5bd8e,0x3dd5bd8e,0x3d8e3dd5,0xbdfb3cc8,0xbcc8bdfb,0xbcc8bdfb,0x3dfbbcc8,0xbcc83dfb,0xbdfbbcc8,0xbdfbbcc8,0x3cc8bdfb,0x3dd53d8e,0xbd8e3dd5,0xbd8e3dd5,0xbdd5bd8e,
0x3dc6bda2,0x3da23dc6,0x3dff3c49,0xbc493dff,0xbd71bde2,0x3de2bd71,0x3d15bdf5,0x3df53d15,0xbdf53d15,0xbd15bdf5,0xbde2bd71,0x3d71bde2,0x3c493dff,0xbdff3c49,0xbda23dc6,0xbdc6bda2,
0x3db53db5,0xbdb53db5,0x3db53db5,0xbdb53db5,0x3db5bdb5,0x3db53db5,0x3db5bdb5,0x3db53db5,0xbdb5bdb5,0x3db5bdb5,0xbdb5bdb5,0x3db5bdb5,0xbdb53db5,0xbdb5bdb5,0xbdb53db5,0xbdb5bdb5,
0xbda23dc6,0xbdc6bda2,0x3c493dff,0xbdff3c49,0x3de23d71,0xbd713de2,0x3df5bd15,0x3d153df5,0x3d15bdf5,0x3df53d15,0xbd71bde2,0x3de2bd71,0xbdffbc49,0x3c49bdff,0xbdc63da2,0xbda2bdc6,
0xbdd5bd8e,0x3d8ebdd5,0xbd8e3dd5,0xbdd5bd8e,0xbcc83dfb,0xbdfbbcc8,0x3dfb3cc8,0xbcc83dfb,0x3dfbbcc8,0x3cc83dfb,0xbcc8bdfb,0x3dfbbcc8,0xbd8ebdd5,0x3dd5bd8e,0xbdd53d8e,0xbd8ebdd5,
0x3d71bde2,0x3de23d71,0xbdf53d15,0xbd15bdf5,0xbdff3c49,0xbc49bdff,0x3dc63da2,0xbda23dc6,0x3da23dc6,0xbdc63da2,0x3c49bdff,0x3dff3c49,0x3d15bdf5,0x3df53d15,0xbde23d71,0xbd71bde2,
0x3ded3d44,0xbd443ded,0xbdedbd44,0x3d44bded,0xbd44bded,0x3dedbd44,0x3d443ded,0xbded3d44,0xbd443ded,0xbdedbd44,0x3d44bded,0x3ded3d44,0x3dedbd44,0x3d443ded,0xbded3d44,0xbd44bded,
0xbd153df5,0xbdf5bd15,0xbd71bde2,0x3de2bd71,0x3dc6bda2,0x3da23dc6,0xbc493dff,0xbdffbc49,0xbdff3c49,0xbc49bdff,0x3da2bdc6,0x3dc63da2,0x3de23d71,0xbd713de2,0xbdf53d15,0xbd15bdf5,
0xbdfbbcc8,0x3cc8bdfb,0x3cc8bdfb,0x3dfb3cc8,0x3dd53d8e,0xbd8e3dd5,0xbd8e3dd5,0xbdd5bd8e,0xbd8ebdd5,0x3dd5bd8e,0x3dd5bd8e,0x3d8e3dd5,0x3cc83dfb,0xbdfb3cc8,0xbdfb3cc8,0xbcc8bdfb,
0x3c49bdff,0x3dff3c49,0x3dc6bda2,0x3da23dc6,0xbd153df5,0xbdf5bd15,0xbde23d71,0xbd71bde2,0x3d71bde2,0x3de23d71,0x3df5bd15,0x3d153df5,0xbda23dc6,0xbdc6bda2,0xbdff3c49,0xbc49bdff,
0x3e000000,0x80003e00,0x3e000000,0x80003e00,0xbe000000,0x8000be00,0xbe000000,0x8000be00,0x3e000000,0x80003e00,0x3e000000,0x80003e00,0xbe000000,0x8000be00,0xbe000000,0x8000be00,
0x3c493dff,0xbdff3c49,0x3dc63da2,0xbda23dc6,0xbd15bdf5,0x3df5bd15,0xbde2bd71,0x3d71bde2,0x3d713de2,0xbde23d71,0x3df53d15,0xbd153df5,0xbda2bdc6,0x3dc6bda2,0xbdffbc49,0x3c49bdff,
0xbdfb3cc8,0xbcc8bdfb,0x3cc83dfb,0xbdfb3cc8,0x3dd5bd8e,0x3d8e3dd5,0xbd8ebdd5,0x3dd5bd8e,0xbd8e3dd5,0xbdd5bd8e,0x3dd53d8e,0xbd8e3dd5,0x3cc8bdfb,0x3dfb3cc8,0xbdfbbcc8,0x3cc8bdfb,
0xbd15bdf5,0x3df5bd15,0xbd713de2,0xbde2bd71,0x3dc63da2,0xbda23dc6,0xbc49bdff,0x3dffbc49,0xbdffbc49,0x3c49bdff,0x3da23dc6,0xbdc63da2,0x3de2bd71,0x3d713de2,0xbdf5bd15,0x3d15bdf5,
0x3dedbd44,0x3d443ded,0xbded3d44,0xbd44bded,0xbd443ded,0xbdedbd44,0x3d44bded,0x3ded3d44,0xbd44bded,0x3dedbd44,0x3d443ded,0xbded3d44,0x3ded3d44,0xbd443ded,0xbdedbd44,0x3d44bded,
0x3d713de2,0xbde23d71,0xbdf5bd15,0x3d15bdf5,0xbdffbc49,0x3c49bdff,0x3dc6bda2,0x3da23dc6,0x3da2bdc6,0x3dc63da2,0x3c493dff,0xbdff3c49,0x3d153df5,0xbdf53d15,0xbde2bd71,0x3d71bde2,
0xbdd53d8e,0xbd8ebdd5,0xbd8ebdd5,0x3dd5bd8e,0xbcc8bdfb,0x3dfbbcc8,0x3dfbbcc8,0x3cc83dfb,0x3dfb3cc8,0xbcc83dfb,0xbcc83dfb,0xbdfbbcc8,0xbd8e3dd5,0xbdd5bd8e,0xbdd5bd8e,0x3d8ebdd5,
0xbda2bdc6,0x3dc6bda2,0x3c49bdff,0x3dff3c49,0x3de2bd71,0x3d713de2,0x3df53d15,0xbd153df5,0x3d153df5,0xbdf53d15,0xbd713de2,0xbde2bd71,0xbdff3c49,0xbc49bdff,0xbdc6bda2,0x3da2bdc6,
0x3db5bdb5,0x3db53db5,0x3db5bdb5,0x3db53db5,0x3db53db5,0xbdb53db5,0x3db53db5,0xbdb53db5,0xbdb53db5,0xbdb5bdb5,0xbdb53db5,0xbdb5bdb5,0xbdb5bdb5,0x3db5bdb5,0xbdb5bdb5,0x3db5bdb5,
0x3dc63da2,0xbda23dc6,0x3dffbc49,0x3c493dff,0xbd713de2,0xbde2bd71,0x3d153df5,0xbdf53d15,0xbdf5bd15,0x3d15bdf5,0xbde23d71,0xbd71bde2,0x3c49bdff,0x3dff3c49,0xbda2bdc6,0x3dc6bda2,
0xbd8e3dd5,0xbdd5bd8e,0x3dd53d8e,0xbd8e3dd5,0xbdfbbcc8,0x3cc8bdfb,0xbcc83dfb,0xbdfbbcc8,0xbcc8bdfb,0x3dfbbcc8,0xbdfb3cc8,0xbcc8bdfb,0x3dd5bd8e,0x3d8e3dd5,0xbd8ebdd5,0x3dd5bd8e,
0xbde2bd71,0x3d71bde2,0x3d153df5,0xbdf53d15,0xbc49bdff,0x3dffbc49,0xbda23dc6,0xbdc6bda2,0x3dc6bda2,0x3da23dc6,0xbdffbc49,0x3c49bdff,0x3df53d15,0xbd153df5,0xbd71bde2,0x3de2bd71,
0x3d44bded,0x3ded3d44,0xbd443ded,0xbdedbd44,0x3dedbd44,0x3d443ded,0xbded3d44,0xbd44bded,0x3ded3d44,0xbd443ded,0xbdedbd44,0x3d44bded,0x3d443ded,0xbded3d44,0xbd44bded,0x3dedbd44,
0x3df53d15,0xbd153df5,0xbde23d71,0xbd71bde2,0x3da23dc6,0xbdc63da2,0xbdffbc49,0x3c49bdff,0x3c493dff,0xbdff3c49,0xbdc6bda2,0x3da2bdc6,0xbd713de2,0xbde2bd71,0xbd15bdf5,0x3df5bd15,
0xbcc83dfb,0xbdfbbcc8,0xbdfbbcc8,0x3cc8bdfb,0xbd8e3dd5,0xbdd5bd8e,0xbdd5bd8e,0x3d8ebdd5,0xbdd53d8e,0xbd8ebdd5,0xbd8ebdd5,0x3dd5bd8e,0xbdfb3cc8,0xbcc8bdfb,0xbcc8bdfb,0x3dfbbcc8,
0xbdffbc49,0x3c49bdff,0xbda2bdc6,0x3dc6bda2,0xbdf5bd15,0x3d15bdf5,0xbd71bde2,0x3de2bd71,0xbde2bd71,0x3d71bde2,0xbd15bdf5,0x3df5bd15,0xbdc6bda2,0x3da2bdc6,0xbc49bdff,0x3dffbc49,
0x3e124925,0,0x3e124925,0,0x3e124925,0,0x3e03cc83,0x3d7de24c,0x3db66a51,0x3de4bdd6,0x3d0234df,0x3e0e9e37,0x3e124576,0x3b034d2c,0x3e123a69,0x3b8349dd,
0x3e122800,0x3bc4e688,0x3e02e551,0x3d82a057,0x3dafed9f,0x3de9c484,0x3cd43110,0x3e0fdc6b,0x3e123a69,0x3b8349dd,0x3e120e3a,0x3c033ca5,0x3e11c4a1,0x3c44b9ec,0x3e01f787,0x3d8648f4,
0x3da94d7d,0x3dee9c1c,0x3ca3983a,0x3e10d96f,0x3e122800,0x3bc4e688,0x3e11c4a1,0x3c44b9ec,0x3e111f35,0x3c9353b8,0x3e010332,0x3d89eacf,0x3da28b42,0x3df343a6,0x3c656a87,0x3e1194d1,
0x3e120e3a,0x3c033ca5,0x3e115dac,0x3c8307ca,0x3e103806,0x3cc407b7,0x3e00085e,0x3d8d85b7,0x3d9ba84a,0x3df7ba31,0x3c033ca5,0x3e120e3a,0x3e11ed1a,0x3c23ff69,0x3e10d96f,0x3ca3983a,
0x3e0f0f7e,0x3cf462e3,0x3dfe0e2f,0x3d91197f,0x3d94a5f9,0x3dfbfed7,0x3b034d2c,0x3e124576,0x3e11c4a1,0x3c44b9ec,0x3e103806,0x3cc407b7,0x3e0da623,0x3d1227a9,0x3dfbfed7,0x3d94a5f9,
0x3d8d85b7,0x3e00085e,0xbb8349dd,0x3e123a69,0x3e1194d1,0x3c656a87,0x3e0f7991,0x3ce44fb9,0x3e0bfc98,0x3d29dba6,0x3df9e2ce,0x3d982af6,0x3d8648f4,0x3e01f787,0xbc23ff69,0x3e11ed1a,
0x3e115dac,0x3c8307ca,0x3e0e9e37,0x3d0234df,0x3e0a139f,0x3d4142ac,0x3df7ba31,0x3d9ba84a,0x3d7de24c,0x3e03cc83,0xbc8307ca,0x3e115dac,0x3e111f35,0x3c9353b8,0x3e0da623,0x3d1227a9,
0x3e07ec15,0x3d58521f,0x3df5851a,0x3d9f1dc8,0x3d6eff8d,0x3e0586f3,0xbcb3d480,0x3e108c5e,0x3e10d96f,0x3ca3983a,0x3e0c9188,0x3d21fd03,0x3e0586f3,0x3d6eff8d,0x3df343a6,0x3da28b42,
0x3d5fecab,0x3e07267f,0xbce44fb9,0x3e0f7991,0x3e108c5e,0x3cb3d480,0x3e0b609d,0x3d31b1bc,0x3e02e551,0x3d82a057,0x3df0f5f2,0x3da5f08d,0x3d50acaf,0x3e08aad2,0xbd0a31bf,0x3e0e25c1,
0x3e103806,0x3cc407b7,0x3e0a139f,0x3d4142ac,0x3e00085e,0x3d8d85b7,0x3dee9c1c,0x3da94d7d,0x3d4142ac,0x3e0a139f,0xbd21fd03,0x3e0c9188,0x3e0fdc6b,0x3cd43110,0x3e08aad2,0x3d50acaf,
0x3df9e2ce,0x3d982af6,0x3dec3643,0x3daca1e6,0x3d31b1bc,0x3e0b609d,0xbd397ee0,0x3e0abd9c,0x3e0f7991,0x3ce44fb9,0x3e07267f,0x3d5fecab,0x3df343a6,0x3da28b42,0x3de9c484,0x3dafed9f,
0x3d21fd03,0x3e0c9188,0xbd50acaf,0x3e08aad2,0x3e0f0f7e,0x3cf462e3,0x3e0586f3,0x3d6eff8d,0x3dec3643,0x3daca1e6,0x3de74700,0x3db3307b,0x3d1227a9,0x3e0da623,0xbd677bf0,0x3e065a1b,
0x3e0e9e37,0x3d0234df,0x3e03cc83,0x3d7de24c,0x3de4bdd6,0x3db66a51,0x3de4bdd6,0x3db66a51,0x3d0234df,0x3e0e9e37,0xbd7de24c,0x3e03cc83,0x3e0e25c1,0x3d0a31bf,0x3e01f787,0x3d8648f4,
0x3ddcddc4,0x3dbfe014,0x3de22928,0x3db99af8,0x3ce44fb9,0x3e0f7991,0xbd89eacf,0x3e010332,0x3e0da623,0x3d1227a9,0x3e00085e,0x3d8d85b7,0x3dd4999d,0x3dc8fee4,0x3ddf8917,0x3dbcc247,
0x3cc407b7,0x3e103806,0xbd94a5f9,0x3dfbfed7,0x3e0d1f63,0x3d1a1637,0x3dfbfed7,0x3d94a5f9,0x3dcbf520,0x3dd1c2a1,0x3ddcddc4,0x3dbfe014,0x3ca3983a,0x3e10d96f,0xbd9f1dc8,0x3df5851a,
0x3e0c9188,0x3d21fd03,0x3df7ba31,0x3d9ba84a,0x3dc2f437,0x3dda2752,0x3dda2752,0x3dc2f437,0x3c8307ca,0x3e115dac,0xbda94d7d,0x3dee9c1c,0x3e0bfc98,0x3d29dba6,0x3df343a6,0x3da28b42,
0x3db99af8,0x3de22928,0x3dd765e4,0x3dc5fe8a,0x3c44b9ec,0x3e11c4a1,0xbdb3307b,0x3de74700,0x3e0b609d,0x3d31b1bc,0x3dee9c1c,0x3da94d7d,0x3dafed9f,0x3de9c484,0x3dd4999d,0x3dc8fee4,
0x3c033ca5,0x3e120e3a,0xbdbcc247,0x3ddf8917,0x3e0abd9c,0x3d397ee0,0x3de9c484,0x3dafed9f,0x3da5f08d,0x3df0f5f2,0x3dd1c2a1,0x3dcbf520,0x3b8349dd,0x3e123a69,0xbdc5fe8a,0x3dd765e4,
0x3e0a139f,0x3d4142ac,0x3de4bdd6,0x3db66a51,0x3d9ba84a,0x3df7ba31,0x3dcee116,0x3dcee116,0,0x3e124925,0xbdcee116,0x3dcee116,0x3e0962ae,0x3d48fcbd,0x3ddf8917,0x3dbcc247,
0x3d91197f,0x3dfe0e2f,0x3dcbf520,0x3dd1c2a1,0xbb8349dd,0x3e123a69,0xbdd765e4,0x3dc5fe8a,0x3e08aad2,0x3d50acaf,0x3dda2752,0x3dc2f437,0x3d8648f4,0x3e01f787,0x3dc8fee4,0x3dd4999d,
0xbc033ca5,0x3e120e3a,0xbddf8917,0x3dbcc247,0x3e07ec15,0x3d58521f,0x3dd4999d,0x3dc8fee4,0x3d767721,0x3e04ad12,0x3dc5fe8a,0x3dd765e4,0xbc44b9ec,0x3e11c4a1,0xbde74700,0x3db3307b,
0x3e07267f,0x3d5fecab,0x3dcee116,0x3dcee116,0x3d5fecab,0x3e07267f,0x3dc2f437,0x3dda2752,0xbc8307ca,0x3e115dac,0xbdee9c1c,0x3da94d7d,0x3e065a1b,0x3d677bf0,0x3dc8fee4,0x3dd4999d,
0x3d48fcbd,0x3e0962ae,0x3dbfe014,0x3ddcddc4,0xbca3983a,0x3e10d96f,0xbdf5851a,0x3d9f1dc8,0x3e0586f3,0x3d6eff8d,0x3dc2f437,0x3dda2752,0x3d31b1bc,0x3e0b609d,0x3dbcc247,0x3ddf8917,
0xbcc407b7,0x3e103806,0xbdfbfed7,0x3d94a5f9,0x3e04ad12,0x3d767721,0x3dbcc247,0x3ddf8917,0x3d1a1637,0x3e0d1f63,0x3db99af8,0x3de22928,0xbce44fb9,0x3e0f7991,0xbe010332,0x3d89eacf,
};

struct Scratch {
    uint8_t X[DF_ * 8192];
    uint32_t Wt[DF_ * 128 * 16];
    uint8_t Z[NCTA * ZSTRIDE];
    uint8_t hn[4 * 256 * 1792];
    float2 rs[S_];
    uint8_t g[4 * 28 * 14336];
    uint32_t cnt[28 * 64];
    uint32_t epoch;
};
__device__ __align__(1024) Scratch g_scr;
#define g_X (scr->X)
#define g_Wt (scr->Wt)
#define g_Z (scr->Z)
#define g_hn (scr->hn)
#define g_g (scr->g)
#define g_cnt (scr->cnt)

#define TS(k, pt, cond)
#define RETRY(i) do {} while (0)

__device__ __forceinline__ uint32_t s2u(const void* p) { return (uint32_t)__cvta_generic_to_shared(p); }
__device__ __forceinline__ void mbar_init(uint32_t a, int c) { asm volatile("mbarrier.init.shared::cta.b64 [%0], %1;" ::"r"(a), "r"(c) : "memory"); }
__device__ __forceinline__ void mbar_expect(uint32_t a, uint32_t b) { asm volatile("mbarrier.arrive.expect_tx.shared::cta.b64 _, [%0], %1;" ::"r"(a), "r"(b) : "memory"); }
__device__ __forceinline__ void mbar_arrive(uint32_t a) { asm volatile("mbarrier.arrive.shared::cta.b64 _, [%0];" ::"r"(a) : "memory"); }
__device__ __forceinline__ void mbar_wait(uint32_t a, uint32_t ph) {
    asm volatile(
        "{\n.reg .pred p;\n.reg .u32 c;\nmov.u32 c, 0;\nW:\n"
        "mbarrier.try_wait.parity.shared::cta.b64 p, [%0], %1;\n@p bra D;\n"
        "add.u32 c, c, 1;\nsetp.lt.u32 p, c, 2000000;\n@p bra W;\nD:\n}" ::"r"(a), "r"(ph)
        : "memory");
}
__device__ __forceinline__ bool elect_one() {
    uint32_t p;
    asm volatile("{.reg .pred p; elect.sync _|p, 0xffffffff; selp.u32 %0, 1, 0, p;}" : "=r"(p));
    return p;
}
constexpr int REPL = 2;
__device__ __forceinline__ void bump(uint32_t* c) {
#pragma unroll
    for (int i = 0; i < REPL; i++) asm volatile("red.relaxed.gpu.global.add.u32 [%0], 1;" ::"l"(c + i * 64) : "memory");
}
__device__ __forceinline__ void store_issued() {
    asm volatile("cp.async.bulk.commit_group;" ::: "memory");
    asm volatile("cp.async.bulk.wait_group.read 0;" ::: "memory");
}
__device__ __forceinline__ uint32_t tagw(uint32_t w, uint32_t keep, uint32_t set) { return (w & keep) | set; }
__device__ __forceinline__ uint32_t lds32(uint32_t a) {
    uint32_t v;
    asm volatile("ld.shared.b32 %0, [%1];" : "=r"(v) : "r"(a) : "memory");
    return v;
}
__device__ __noinline__ void patch_chunks(uint32_t sa, const uint8_t* gp, uint32_t tw, uint32_t tagv, uint32_t badmask) {
#pragma unroll 1
    for (int i = 0; i < 4; i++) {
        if (!((badmask >> i) & 1)) continue;
        uint4 a;
        uint32_t v;
        int att = 0;
        do {
            asm volatile("ld.relaxed.gpu.global.v4.b32 {%0,%1,%2,%3}, [%4];" : "=r"(a.x), "=r"(a.y), "=r"(a.z), "=r"(a.w) : "l"(gp + i * 2048) : "memory");
            v = tw == 0 ? a.x : tw == 1 ? a.y : tw == 2 ? a.z : a.w;
        } while (((v ^ tagv) & 1) && ++att < 1000000);
        asm volatile("st.shared.v4.b32 [%0], {%1,%2,%3,%4};" ::"r"(sa + i * 2048), "r"(a.x), "r"(a.y), "r"(a.z), "r"(a.w) : "memory");
        asm volatile("st.shared.b32 [%0], %1;" ::"r"(sa + i * 2048 + tw * 4), "r"(v & ~1u) : "memory");
    }
    asm volatile("fence.proxy.async.shared::cta;" ::: "memory");
}
__device__ __noinline__ void patch_zero(uint32_t sa, const uint8_t* gp) {
#pragma unroll 1
    for (int i = 0; i < 7; i++) {
        uint4 a;
        int att = 0;
        do {
            asm volatile("ld.relaxed.gpu.global.v4.b32 {%0,%1,%2,%3}, [%4];" : "=r"(a.x), "=r"(a.y), "=r"(a.z), "=r"(a.w) : "l"(gp + i * 2048) : "memory");
        } while (!(a.x && a.y && a.z && a.w) && ++att < 1000000);
        asm volatile("st.shared.v4.b32 [%0], {%1,%2,%3,%4};" ::"r"(sa + i * 2048), "r"(a.x), "r"(a.y), "r"(a.z), "r"(a.w) : "memory");
    }
    asm volatile("fence.proxy.async.shared::cta;" ::: "memory");
}
__device__ __forceinline__ bool check_chunks(uint32_t sa, const uint8_t* gp, uint32_t tw, uint32_t tagv, bool last) {
    const uint32_t ca = sa + tw * 4;
    const uint32_t c0 = lds32(ca), c1 = lds32(ca + 2048), c2 = lds32(ca + 4096), c3 = last ? lds32(ca + 6144) : tagv;
    if (tagv) {
        asm volatile("st.shared.b32 [%0], %1;" ::"r"(ca), "r"(c0 & ~1u) : "memory");
        asm volatile("st.shared.b32 [%0], %1;" ::"r"(ca + 2048), "r"(c1 & ~1u) : "memory");
        asm volatile("st.shared.b32 [%0], %1;" ::"r"(ca + 4096), "r"(c2 & ~1u) : "memory");
        asm volatile("st.shared.b32 [%0], %1;" ::"r"(ca + 6144), "r"(c3 & ~1u) : "memory");
        asm volatile("fence.proxy.async.shared::cta;" ::: "memory");
    }
    const bool bad = ((c0 ^ tagv) | (c1 ^ tagv) | (c2 ^ tagv) | (c3 ^ tagv)) & 1;
    if (bad) patch_chunks(sa, gp, tw, tagv, ((c0 ^ tagv) & 1) | (((c1 ^ tagv) & 1) << 1) | (((c2 ^ tagv) & 1) << 2) | (((c3 ^ tagv) & 1) << 3));
    return bad;
}
__device__ __forceinline__ bool mbar_try(uint32_t a, uint32_t ph) {
    uint32_t ok;
    asm volatile("{.reg .pred p; mbarrier.test_wait.parity.shared::cta.b64 p, [%1], %2; selp.u32 %0, 1, 0, p;}" : "=r"(ok) : "r"(a), "r"(ph) : "memory");
    return ok;
}
__device__ __forceinline__ void tma_st_2d(const CUtensorMap* tm, uint32_t src, int c0, int c1) {
    asm volatile("cp.async.bulk.tensor.2d.global.shared::cta.bulk_group [%0, {%2, %3}], [%1];" ::"l"(tm), "r"(src), "r"(c0), "r"(c1) : "memory");
}
__device__ __forceinline__ void sts64(uint32_t a, uint32_t x, uint32_t y) { asm volatile("st.shared.v2.b32 [%0], {%1,%2};" ::"r"(a), "r"(x), "r"(y) : "memory"); }
__device__ __forceinline__ void cnt_wait(const uint32_t* c, uint32_t target) {
    asm volatile(
        "{\n.reg .pred p;\n.reg .u32 c, v;\nmov.u32 c, 0;\nW:\n"
        "ld.acquire.gpu.global.u32 v, [%0];\nsetp.ge.u32 p, v, %1;\n@p bra D;\n"
        "add.u32 c, c, 1;\nsetp.lt.u32 p, c, 2000000;\n@p bra W;\nD:\n}" ::"l"(c), "r"(target)
        : "memory");
    asm volatile("fence.proxy.async.global;" ::: "memory");
}
__device__ __forceinline__ void hint_poll(const uint32_t* c, uint32_t target) {
    asm volatile(
        "{\n.reg .pred p;\n.reg .u32 c, v;\nmov.u32 c, 0;\nW:\n"
        "ld.relaxed.gpu.global.u32 v, [%0];\nsetp.ge.u32 p, v, %1;\n@p bra D;\n"
        "add.u32 c, c, 1;\nsetp.lt.u32 p, c, 2000000;\n@p bra W;\nD:\n}" ::"l"(c + (blockIdx.x % REPL) * 64), "r"(target)
        : "memory");
}
__device__ __forceinline__ void cnt_wait_r(const uint32_t* c, uint32_t target) { cnt_wait(c + (blockIdx.x % REPL) * 64, target); }
__device__ __forceinline__ void fence_async_smem() { asm volatile("fence.proxy.async.shared::cta;" ::: "memory"); }
__device__ __forceinline__ void bulk_g2s(uint32_t dst, const void* src, uint32_t bytes, uint32_t mbar) {
    asm volatile("cp.async.bulk.shared::cluster.global.mbarrier::complete_tx::bytes [%0], [%1], %2, [%3];" ::"r"(dst), "l"(src), "r"(bytes), "r"(mbar) : "memory");
}
__device__ __forceinline__ void tma_2d(uint32_t dst, const CUtensorMap* tm, int c0, int c1, uint32_t mbar) {
    asm volatile("cp.async.bulk.tensor.2d.shared::cluster.global.mbarrier::complete_tx::bytes [%0], [%1, {%3, %4}], [%2];" ::"r"(dst), "l"(tm), "r"(mbar), "r"(c0), "r"(c1) : "memory");
}
__device__ __forceinline__ void tma_pf_2d(const CUtensorMap* tm, int c0, int c1) {
    asm volatile("cp.async.bulk.prefetch.tensor.2d.L2.global [%0, {%1, %2}];" ::"l"(tm), "r"(c0), "r"(c1) : "memory");
}
__device__ __forceinline__ void l2_prefetch(const void* p, uint32_t bytes) { asm volatile("cp.async.bulk.prefetch.L2.global [%0], %1;" ::"l"(p), "r"(bytes) : "memory"); }
template <int ID, int N> __device__ __forceinline__ void bar_sync() { asm volatile("bar.sync %0, %1;" ::"n"(ID), "n"(N) : "memory"); }
template <int ID, int N> __device__ __forceinline__ void bar_arrive() { asm volatile("bar.arrive %0, %1;" ::"n"(ID), "n"(N) : "memory"); }
__device__ __forceinline__ void wg_fence() { asm volatile("wgmma.fence.sync.aligned;" ::: "memory"); }
__device__ __forceinline__ void wg_commit() { asm volatile("wgmma.commit_group.sync.aligned;" ::: "memory"); }
template <int N> __device__ __forceinline__ void wg_wait() { asm volatile("wgmma.wait_group.sync.aligned %0;" ::"n"(N) : "memory"); }

__device__ __forceinline__ uint64_t mk_desc(uint32_t addr, uint32_t lbo, uint32_t sbo, uint32_t swz) {
    return (uint64_t)((addr & 0x3FFFF) >> 4) | ((uint64_t)(lbo >> 4) << 16) | ((uint64_t)(sbo >> 4) << 32) | ((uint64_t)swz << 62);
}
__device__ __forceinline__ uint32_t pack_h2(float lo, float hi) {
    uint32_t r;
    asm("cvt.rn.f16x2.f32 %0, %1, %2;" : "=r"(r) : "f"(hi), "f"(lo));
    return r;
}
__device__ __forceinline__ uint32_t pack_b2(float lo, float hi) {
    uint32_t r;
    asm("cvt.rn.bf16x2.f32 %0, %1, %2;" : "=r"(r) : "f"(hi), "f"(lo));
    return r;
}
__device__ __forceinline__ float bf_lo(uint32_t v) { return __uint_as_float(v << 16); }
__device__ __forceinline__ float bf_hi(uint32_t v) { return __uint_as_float(v & 0xffff0000u); }
__device__ __forceinline__ uint4 ldg128_pinned(const void* p) {
    uint4 v;
    asm volatile("ld.global.nc.v4.b32 {%0,%1,%2,%3}, [%4];" : "=r"(v.x), "=r"(v.y), "=r"(v.z), "=r"(v.w) : "l"(p) : "memory");
    return v;
}
#define ld_tab(word_off) ldg128_pinned(tab + (word_off))
__device__ __forceinline__ void sts32(uint32_t a, uint32_t v) { asm volatile("st.shared.b32 [%0], %1;" ::"r"(a), "r"(v) : "memory"); }
__device__ __forceinline__ void sts128(uint32_t a, uint32_t x, uint32_t y, uint32_t z, uint32_t w) {
    asm volatile("st.shared.v4.b32 [%0], {%1,%2,%3,%4};" ::"r"(a), "r"(x), "r"(y), "r"(z), "r"(w) : "memory");
}
__device__ __forceinline__ uint4 lds128(uint32_t a) {
    uint4 v;
    asm volatile("ld.shared.v4.b32 {%0,%1,%2,%3}, [%4];" : "=r"(v.x), "=r"(v.y), "=r"(v.z), "=r"(v.w) : "r"(a) : "memory");
    return v;
}
__device__ __forceinline__ void stg32(void* p, uint32_t v) { asm volatile("st.global.b32 [%0], %1;" ::"l"(p), "r"(v) : "memory"); }
__device__ __forceinline__ void stg128(void* p, const uint4& v) {
    asm volatile("st.global.v4.b32 [%0], {%1,%2,%3,%4};" ::"l"(p), "r"(v.x), "r"(v.y), "r"(v.z), "r"(v.w) : "memory");
}
__device__ __forceinline__ float gelu_tanh(float u) {
    float th;
    const float z = u * fmaf(u * u, 0.03567740813f, 0.7978845608f);
    asm("tanh.approx.f32 %0, %1;" : "=f"(th) : "f"(z));
    const float hu = 0.5f * u;
    return fmaf(hu, th, hu);
}
__device__ __forceinline__ uint32_t clk32() {
    uint32_t c;
    asm volatile("mov.u32 %0, %%clock;" : "=r"(c));
    return c;
}
__device__ __forceinline__ void pace_until(uint32_t t) {
    int it = 0;
    while ((int)(clk32() - t) < 0 && ++it < 100000) __nanosleep(40);
}
__device__ __forceinline__ void spin_until(uint32_t t) {
    int it = 0;
    while ((int)(clk32() - t) < 0 && ++it < 100000) {}
}
__device__ __forceinline__ void ldsm4t(uint32_t a, uint32_t& r0, uint32_t& r1, uint32_t& r2, uint32_t& r3) {
    asm volatile("ldmatrix.sync.aligned.m8n8.x4.trans.shared.b16 {%0,%1,%2,%3}, [%4];" : "=r"(r0), "=r"(r1), "=r"(r2), "=r"(r3) : "r"(a) : "memory");
}
__device__ __forceinline__ void stsm4(uint32_t a, uint32_t r0, uint32_t r1, uint32_t r2, uint32_t r3) {
    asm volatile("stmatrix.sync.aligned.m8n8.x4.shared.b16 [%0], {%1,%2,%3,%4};" ::"r"(a), "r"(r0), "r"(r1), "r"(r2), "r"(r3) : "memory");
}
__device__ __forceinline__ void ldsm2t(uint32_t a, uint32_t& r0, uint32_t& r1) {
    asm volatile("ldmatrix.sync.aligned.m8n8.x2.trans.shared.b16 {%0,%1}, [%2];" : "=r"(r0), "=r"(r1) : "r"(a) : "memory");
}

#define R4(d, o) "+f"(d[o]), "+f"(d[o + 1]), "+f"(d[o + 2]), "+f"(d[o + 3])
#define R8(d, o) R4(d, o), R4(d, o + 4)
#define R16(d, o) R8(d, o), R8(d, o + 8)

#define WGMMA_N32_RS(NAME, TY)                                                                                          \
    template <int TB, int SD>                                                                                           \
    __device__ __forceinline__ void NAME(float (&d)[16], const uint4& a, uint64_t db) {                                 \
        asm volatile("wgmma.mma_async.sync.aligned.m64n32k16.f32." TY "." TY " "                                        \
                     "{%0,%1,%2,%3,%4,%5,%6,%7,%8,%9,%10,%11,%12,%13,%14,%15}, {%16,%17,%18,%19}, %20, %21, 1, 1, %22;" \
                     : R16(d, 0)                                                                                        \
                     : "r"(a.x), "r"(a.y), "r"(a.z), "r"(a.w), "l"(db), "n"(SD), "n"(TB));                              \
    }
WGMMA_N32_RS(wg_n32_h, "f16")
WGMMA_N32_RS(wg_n32_b, "bf16")

#define WGMMA_N64_RS(NAME, TY)                                                                                          \
    template <int TB, int SD>                                                                                           \
    __device__ __forceinline__ void NAME(float (&d)[32], const uint4& a, uint64_t db) {                                 \
        asm volatile("wgmma.mma_async.sync.aligned.m64n64k16.f32." TY "." TY " "                                        \
                     "{%0,%1,%2,%3,%4,%5,%6,%7,%8,%9,%10,%11,%12,%13,%14,%15,"                                          \
                     "%16,%17,%18,%19,%20,%21,%22,%23,%24,%25,%26,%27,%28,%29,%30,%31}, {%32,%33,%34,%35}, %36, %37, 1, 1, %38;" \
                     : R16(d, 0), R16(d, 16)                                                                            \
                     : "r"(a.x), "r"(a.y), "r"(a.z), "r"(a.w), "l"(db), "n"(SD), "n"(TB));                              \
    }
WGMMA_N64_RS(wg_n64_h, "f16")
WGMMA_N64_RS(wg_n64_b, "bf16")

template <int TB>
__device__ __forceinline__ void wg_n112_ss(float (&d)[56], uint64_t da, uint64_t db) {
    asm volatile("wgmma.mma_async.sync.aligned.m64n112k16.f32.bf16.bf16 "
                 "{%0,%1,%2,%3,%4,%5,%6,%7,%8,%9,%10,%11,%12,%13,%14,%15,"
                 "%16,%17,%18,%19,%20,%21,%22,%23,%24,%25,%26,%27,%28,%29,%30,%31,"
                 "%32,%33,%34,%35,%36,%37,%38,%39,%40,%41,%42,%43,%44,%45,%46,%47,"
                 "%48,%49,%50,%51,%52,%53,%54,%55}, %56, %57, 1, 1, 1, 1, %58;"
                 : R16(d, 0), R16(d, 16), R16(d, 32), R8(d, 48)
                 : "l"(da), "l"(db), "n"(TB));
}

__device__ __forceinline__ void wg_n56_ss(float (&d)[28], uint64_t da, uint64_t db) {
    asm volatile("wgmma.mma_async.sync.aligned.m64n56k16.f32.bf16.bf16 "
                 "{%0,%1,%2,%3,%4,%5,%6,%7,%8,%9,%10,%11,%12,%13,%14,%15,"
                 "%16,%17,%18,%19,%20,%21,%22,%23,%24,%25,%26,%27}, %28, %29, 1, 1, 1, 1, 0;"
                 : R16(d, 0), R8(d, 16), R4(d, 24)
                 : "l"(da), "l"(db));
}

constexpr float C1 = 0.62348980185873353f, C2 = -0.22252093395631440f, C3 = -0.90096886790241913f;
constexpr float S1 = 0.78183148246802981f, S2 = 0.97492791218182361f, S3 = 0.43388373911755812f;

constexpr int WS = 14, AS = 8;
constexpr int WB = 8192, AB = 14336;
constexpr int SM_W = 0, SM_A = WS * WB;
constexpr int SM_T = SM_A, SM_X = SM_T + 16384, SM_WF = SM_X + 16384, SM_G = SM_WF + 16384, SM_Z = SM_G + 16384, SM_XS = SM_Z + 16384, SM_S = SM_XS + 16384;
constexpr int XS_PITCH = 912;
constexpr int W_DELAY = 1300;
constexpr int EV_DELAY = 300;
constexpr int PACE_RING = 250, PACE_PF1 = 300, PACE_PF = 750, ZDELAY = 2500;
constexpr int C_X = 0, C_W = 4, C_Z = 8, C_H = 12, C_H0 = 14, C_G = 16, C_G0 = 20, C_G1 = 24;
constexpr int SM_RED = SM_A + AS * AB;
constexpr int SM_BAR = SM_RED + 1024;
constexpr int SM_TRACE = SM_BAR + 640;
constexpr int SM_TOTAL = SM_TRACE + 512;
static_assert(SM_S + 16384 <= SM_RED, "fft buffers must fit inside the activation ring");
constexpr int B_WFULL = 0, B_WEMPTY = WS, B_AFULL = 2 * WS, B_AEMPTY = 2 * WS + AS, B_X0 = 2 * WS + 2 * AS, B_WF0 = B_X0 + 2, B_G = B_WF0 + 2, B_Z = B_G + 1, B_GO = B_Z + 2, B_EV = B_GO + 1, B_RES = B_EV + 3, B_OWN = B_RES + 1, B_EARLY = B_OWN + 1, B_XS = B_EARLY + 8;

__device__ __forceinline__ void mbar_wait2(uint32_t a, uint32_t pa, uint32_t b, uint32_t pb) {
    asm volatile(
        "{\n.reg .pred p, q;\n.reg .u32 c;\nmov.u32 c, 0;\nW:\n"
        "mbarrier.try_wait.parity.shared::cta.b64 p, [%0], %1;\n"
        "mbarrier.try_wait.parity.shared::cta.b64 q, [%2], %3;\n"
        "and.pred p, p, q;\n@p bra D;\n"
        "add.u32 c, c, 1;\nsetp.lt.u32 p, c, 2000000;\n@p bra W;\nD:\n}" ::"r"(a), "r"(pa), "r"(b), "r"(pb)
        : "memory");
}
template <int MODE>
__device__ __forceinline__ void gemm_loop(float (&acc)[56], uint32_t sb, int wi, int ai, int niter) {
    const uint32_t bar = sb + SM_BAR;
    wg_fence();
    wg_commit();
    wg_wait<0>();
    int ws = wi % WS, wph = (wi / WS) & 1, as = ai % AS, aph = (ai / AS) & 1, pw = 0, pa = 0;
    const uint64_t dA0 = mk_desc(sb + SM_W, 16, 1024, 1);
    const uint64_t dB0 = MODE ? mk_desc(sb + SM_A, 128, 1024, 0) : mk_desc(sb + SM_A, 1792, 128, 0);
#pragma unroll
    for (int i = 0; i < 56; i++) asm volatile("" : "+f"(acc[i])::"memory");
    bool ok0 = false, ok1 = false;
#pragma unroll 1
    for (int it = 0; it < niter; it++) {
        const uint64_t da = dA0 + (uint64_t)(ws * (WB >> 4)), db = dB0 + (uint64_t)(as * (AB >> 4));
        int nw = ws + 2, nwph = wph, na = as + 2, naph = aph;
        if (nw == WS) { nw = 0; nwph ^= 1; }
        if (na == AS) { na = 0; naph ^= 1; }
#pragma unroll
        for (int h = 0; h < 2; h++) {
            if (!ok0) mbar_wait(bar + 8 * (B_WFULL + ws + h), wph);
            if (!ok1) mbar_wait(bar + 8 * (B_AFULL + as + h), aph);
            TS(3 + MODE, 7, it == 0 && h == 0 && (threadIdx.x & 127) == 0);
            wg_fence();
#pragma unroll
            for (int ks = 0; ks < 4; ks++) {
                wg_n112_ss<MODE>(acc, da + h * (WB >> 4) + ks * 128, db + h * (AB >> 4) + ks * (MODE ? 16 : 224));
                if (ks == 1) {
                    ok0 = mbar_try(bar + 8 * (B_WFULL + (h ? nw : ws + 1)), h ? nwph : wph);
                    ok1 = mbar_try(bar + 8 * (B_AFULL + (h ? na : as + 1)), h ? naph : aph);
                }
            }
            wg_commit();
            wg_wait<1>();
            if ((h || it > 0) && elect_one()) {
                mbar_arrive(bar + 8 * (B_WEMPTY + (h ? ws : pw + 1)));
                mbar_arrive(bar + 8 * (B_AEMPTY + (h ? as : pa + 1)));
            }
        }
        pw = ws; pa = as;
        ws = nw; wph = nwph; as = na; aph = naph;
    }
    wg_wait<0>();
#pragma unroll
    for (int i = 0; i < 56; i++) asm volatile("" : "+f"(acc[i])::"memory");
    if (MODE == 0 && elect_one()) {
        mbar_arrive(bar + 8 * (B_WEMPTY + pw + 1));
        mbar_arrive(bar + 8 * (B_AEMPTY + pa + 1));
    }
}

__device__ __forceinline__ void gemm_half(float (&acc)[28], uint32_t sb, int q) {
    const uint32_t bar = sb + SM_BAR;
    wg_fence();
    wg_commit();
    wg_wait<0>();
    int ws = 2 * q, wph = 0, as = q, aph = 0, pw = 0, pa = 0;
    const uint64_t dA0 = mk_desc(sb + SM_W, 16, 1024, 1), dB0 = mk_desc(sb + SM_A, 896, 128, 0);
#pragma unroll
    for (int i = 0; i < 28; i++) {
        acc[i] = 0.f;
        asm volatile("" : "+f"(acc[i])::"memory");
    }
#pragma unroll 1
    for (int it = 0; it < 8; it++) {
        mbar_wait2(bar + 8 * (B_WFULL + ws), wph, bar + 8 * (B_WFULL + ws + 1), wph);
        mbar_wait(bar + 8 * (B_AFULL + as), aph);
        const uint64_t da = dA0 + (uint64_t)(ws * (WB >> 4)), db = dB0 + (uint64_t)(as * (AB >> 4));
        wg_fence();
#pragma unroll
        for (int ks = 0; ks < 4; ks++) wg_n56_ss(acc, da + ks * 128, db + ks * 112);
        wg_commit();
        wg_wait<1>();
        if (it > 0 && elect_one()) {
            mbar_arrive(bar + 8 * (B_WEMPTY + pw + 1));
            mbar_arrive(bar + 8 * (B_AEMPTY + pa));
        }
        wg_fence();
#pragma unroll
        for (int ks = 4; ks < 8; ks++) wg_n56_ss(acc, da + ks * 128, db + ks * 112);
        wg_commit();
        wg_wait<1>();
        if (elect_one()) mbar_arrive(bar + 8 * (B_WEMPTY + ws));
        pw = ws; pa = as;
        ws += 4; if (ws >= WS) { ws -= WS; wph ^= 1; }
        as += 2; if (as >= AS) { as -= AS; aph ^= 1; }
    }
    wg_wait<0>();
#pragma unroll
    for (int i = 0; i < 28; i++) asm volatile("" : "+f"(acc[i])::"memory");
    if (elect_one()) mbar_arrive(bar + 8 * (B_WEMPTY + pw + 1));
}

__device__ __forceinline__ int col_pos(int c, int q) { return c < 104 ? 2 * c + q : c == 104 ? (q ? -1 : 208) : c < 113 ? 14 + 2 * c + q : -1; }

__global__ void __launch_bounds__(384, 1)
    fused_kernel(const __nv_bfloat16* __restrict__ x, const uint32_t* __restrict__ tab, Scratch* __restrict__ scr, const __nv_bfloat16* __restrict__ wr, const __nv_bfloat16* __restrict__ wi,
                 const __nv_bfloat16* __restrict__ w2, const __nv_bfloat16* __restrict__ b1, const __nv_bfloat16* __restrict__ b2,
                 __nv_bfloat16* __restrict__ out, const __grid_constant__ CUtensorMap tm1, const __grid_constant__ CUtensorMap tm2,
                 const __grid_constant__ CUtensorMap tmx, const __grid_constant__ CUtensorMap tmw, const __grid_constant__ CUtensorMap tmz,
                 const __grid_constant__ CUtensorMap tmh) {
    extern __shared__ __align__(1024) uint8_t smem_raw[];
    uint32_t sb = s2u(smem_raw);
    const int tid = threadIdx.x, lane = tid & 31, cta = blockIdx.x;
    TS(0, 0, tid == 0);
    uint32_t xv[2][7];
    uint4 af1[8];
    float twc1[2][3], tws1[2][3];
    uint32_t tag;
    if (tid < 256) {
        const uint32_t* xr = reinterpret_cast<const uint32_t*>(x) + (cta * 16 + (tid >> 5) * 2) * 224 + lane;
#pragma unroll
        for (int rr = 0; rr < 2; rr++)
#pragma unroll
            for (int m = 0; m < 7; m++) asm volatile("ld.global.nc.b32 %0, [%1];" : "=r"(xv[rr][m]) : "l"(xr + rr * 224 + m * 32));
        {
            const int g = lane >> 2;
            const float wa = (float)(8 * ((tid >> 5) & 3) + (g & 1) + ((g & 2) << 1) + ((g & 4) >> 1)) * (6.283185307179586f / 64.f);
            const float a0 = wa * (float)(2 * (lane & 3));
#pragma unroll
            for (int i = 0; i < 8; i++) {
                uint32_t f[4];
#pragma unroll
                for (int hh = 0; hh < 2; hh++) {
                    const float ang = fmaf(wa, (float)(16 * (i & 3) + 8 * hh + (i >> 2)), a0);
                    float c, s;
                    asm volatile("cos.approx.ftz.f32 %0, %1;" : "=f"(c) : "f"(ang));
                    asm volatile("sin.approx.ftz.f32 %0, %1;" : "=f"(s) : "f"(ang));
                    f[2 * hh] = pack_h2(c, s);
                    f[2 * hh + 1] = pack_h2(-s, c);
                }
                af1[i] = make_uint4(f[0], f[1], f[2], f[3]);
                asm volatile("" : "+r"(af1[i].x), "+r"(af1[i].y), "+r"(af1[i].z), "+r"(af1[i].w));
            }
        }
#pragma unroll
        for (int e = 0; e < 2; e++)
#pragma unroll
            for (int b = 0; b < 3; b++) {
                const float ang = (float)(2 * lane + e) * ((b + 1) * 6.283185307179586f / 448.f);
                asm volatile("cos.approx.ftz.f32 %0, %1;" : "=f"(twc1[e][b]) : "f"(ang));
                asm volatile("sin.approx.ftz.f32 %0, %1;" : "=f"(tws1[e][b]) : "f"(ang));
            }
    }
    asm volatile("" : "+r"(sb));
    sb = __shfl_sync(0xffffffffu, sb, 0);
    const uint32_t bar = sb + SM_BAR;
    const int warp = __shfl_sync(0xffffffffu, tid >> 5, 0);
    const int dt = cta & 3;
    const bool g1_half = cta >= 96;
    const int mt1 = g1_half ? (cta >> 2) & 3 : 27 - (cta >> 2);
#define TAG ((tag + 1) & 1)

    if (warp < 8) {
        const int q = warp >> 2, w = warp & 3, g = lane >> 2, t = lane & 3, tl = tid & 127;
        {
            float R[2][2][4], I[2][2][3], sum[2], sq[2];
#pragma unroll
            for (int rr = 0; rr < 2; rr++) {
                float ss = 0.f;
#pragma unroll
                for (int e = 0; e < 2; e++) {
                    float v[7];
#pragma unroll
                    for (int m = 0; m < 7; m++) {
                        v[m] = e ? bf_hi(xv[rr][m]) : bf_lo(xv[rr][m]);
                        ss = fmaf(v[m], v[m], ss);
                    }
                    const float s1 = v[1] + v[6], s2 = v[2] + v[5], s3 = v[3] + v[4];
                    const float d1 = v[1] - v[6], d2 = v[2] - v[5], d3 = v[3] - v[4];
                    R[rr][e][0] = (v[0] + s1) + (s2 + s3);
                    R[rr][e][1] = fmaf(C3, s3, fmaf(C2, s2, fmaf(C1, s1, v[0])));
                    R[rr][e][2] = fmaf(C1, s3, fmaf(C3, s2, fmaf(C2, s1, v[0])));
                    R[rr][e][3] = fmaf(C2, s3, fmaf(C1, s2, fmaf(C3, s1, v[0])));
                    I[rr][e][0] = fmaf(S3, d3, fmaf(S2, d2, S1 * d1));
                    I[rr][e][1] = fmaf(-S1, d3, fmaf(-S3, d2, S2 * d1));
                    I[rr][e][2] = fmaf(S2, d3, fmaf(-S1, d2, S3 * d1));
                }
                sum[rr] = R[rr][0][0] + R[rr][1][0];
                sq[rr] = ss;
            }
#pragma unroll
            for (int o = 16; o > 0; o >>= 1) {
#pragma unroll
                for (int rr = 0; rr < 2; rr++) {
                    sum[rr] += __shfl_xor_sync(0xffffffffu, sum[rr], o);
                    sq[rr] += __shfl_xor_sync(0xffffffffu, sq[rr], o);
                }
            }
#pragma unroll
            for (int rr = 0; rr < 2; rr++)
#pragma unroll
                for (int b = 0; b < 3; b++)
#pragma unroll
                    for (int e = 0; e < 2; e++) {
                        const float c = twc1[e][b], s = tws1[e][b];
                        const float re = R[rr][e][b + 1], im = I[rr][e][b];
                        R[rr][e][b + 1] = fmaf(re, c, -im * s);
                        I[rr][e][b] = fmaf(re, s, im * c);
                    }
#pragma unroll
            for (int rr = 0; rr < 2; rr++) {
                const float mean = sum[rr] * (1.f / 448.f);
                const float var = fmaxf(fmaf(-mean, mean, sq[rr] * (1.f / 448.f)), 0.f);
                const float rstd = 0.125f * rsqrtf(var + 1e-5f);
                const float m7 = -7.f * mean * rstd;
                const int nl = 8 * (warp & 1) + 2 * (warp >> 1) + rr;
                const uint32_t base = sb + SM_T + nl * 128 + (((lane >> 2) ^ (nl & 7)) << 4) + (lane & 3) * 4;
#pragma unroll
                for (int e = 0; e < 2; e++) {
                    sts32(base + e * 8192, pack_h2(fmaf(R[rr][e][0], rstd, m7), 0.f));
#pragma unroll
                    for (int b = 0; b < 3; b++) sts32(base + e * 8192 + (b + 1) * 2048, pack_h2(R[rr][e][b + 1] * rstd, -I[rr][e][b] * rstd));
                }
            }
            TS(0, 2, tid == 0);
            fence_async_smem();
            bar_sync<11, 288>();
            tag = lds32(bar + 632);
            float ev[16], od[16];
            const uint64_t db = mk_desc(sb + SM_T + q * 4096, 16, 1024, 1);
            wg_fence();
            wg_n32_h<0, 0>(ev, af1[0], db);
            wg_n32_h<0, 0>(od, af1[4], db + 512);
#pragma unroll
            for (int ks = 1; ks < 4; ks++) {
                wg_n32_h<0, 1>(ev, af1[ks], db + ks * 2);
                wg_n32_h<0, 1>(od, af1[4 + ks], db + 512 + ks * 2);
            }
            wg_commit();
            const int cl = 8 * w + (g & 1) + ((g & 2) << 1) + ((g & 4) >> 1);
            const int hsw = ((t >> 1) ^ (cta >> 3)) & 1;
            const uint32_t dre = sb + SM_S + cl * 64 + ((hsw ^ ((cl >> 1) & 3)) << 4) + (t & 1) * 8, dim = dre ^ 32;
            const uint32_t tm = (t & 1) == ((cta >> 3) & 1);
            wg_wait<0>();
            TS(0, 3, tid == 0);
#pragma unroll
            for (int bl = 0; bl < 2; bl++) {
                const int mb = (2 * q + bl + 3) & 3;
                const uint32_t d0 = mb * 4096;
                const int o = 8 * bl;
                sts64(dre + d0, tagw(pack_h2(ev[o] + od[o], ev[o + 1] + od[o + 1]), ~tm, tm & TAG), pack_h2(ev[o + 4] + od[o + 4], ev[o + 5] + od[o + 5]));
                sts64(dim + d0, tagw(pack_h2(ev[o + 2] + od[o + 2], ev[o + 3] + od[o + 3]), ~tm, tm & TAG), pack_h2(ev[o + 6] + od[o + 6], ev[o + 7] + od[o + 7]));
                sts64(dre + d0 + 2048, tagw(pack_h2(ev[o] - od[o], ev[o + 1] - od[o + 1]), ~tm, tm & TAG), pack_h2(ev[o + 4] - od[o + 4], ev[o + 5] - od[o + 5]));
                sts64(dim + d0 + 2048, tagw(pack_h2(od[o + 2] - ev[o + 2], od[o + 3] - ev[o + 3]), ~tm, tm & TAG), pack_h2(od[o + 6] - ev[o + 6], od[o + 7] - ev[o + 7]));
            }
            fence_async_smem();
            bar_sync<1, 256>();
            TS(0, 4, tid == 0);
            if (warp == 0 && elect_one()) {
                tma_st_2d(&tmx, sb + SM_S, (cta & 3) * 512 + (cta >> 2) * 16, 0);
                store_issued();
                bump(&g_cnt[C_X * 64]);
                mbar_arrive(bar + 8 * B_GO);
                TS(0, 6, true);
            }
        }
        const int cpos = col_pos(cta, q);
        if (cpos >= 0) {
            uint4 af[8], tw[8];
#pragma unroll
            for (int i = 0; i < 8; i++) af[i] = ld_tab(TOFF_A2 + (i * 128 + tl) * 4);
#pragma unroll
            for (int i = 0; i < 8; i++) tw[i] = ld_tab(TOFF_TW2 + (i * 128 + tl) * 4);
            const uint32_t xa = sb + SM_X + q * 8192;
            const uint64_t dx = mk_desc(xa, 16, 512, 2), dx1 = mk_desc(xa, 2048, 256, 3);
            const uint64_t dg = mk_desc(sb + SM_G, 16, 1024, 1);
            if (cpos == 192 || cpos == 208) {
#pragma unroll
                for (int i = 0; i < 8; i++) {
                    tw[i].x = __float_as_uint(__uint_as_float(tw[i].x) * 0.70710678118654752f);
                    tw[i].y = __float_as_uint(__uint_as_float(tw[i].y) * 0.70710678118654752f);
                    tw[i].z = __float_as_uint(__uint_as_float(tw[i].z) * 0.70710678118654752f);
                    tw[i].w = __float_as_uint(__uint_as_float(tw[i].w) * 0.70710678118654752f);
                }
            }
            mbar_wait(bar + 8 * B_G, 0);
            const int apc = 2 * (cpos & 31) + ((cpos >> 5) & 1);
            {
                mbar_wait(bar + 8 * (B_X0 + q), 0);
                TS(1, 0, tid == 0);
                if (check_chunks(xa + tl * 16, g_X + (size_t)((cpos & ~63) + apc) * 8192 + tl * 16, ((lane >> 3) & 1) * 2, TAG, true)) RETRY(0);
                if (q) bar_sync<3, 128>(); else bar_sync<2, 128>();
            }
            float ev[16], od[16];
            wg_fence();
            wg_n32_h<1, 0>(ev, af[0], dx1);
            wg_n32_h<1, 0>(od, af[4], dx1 + 256);
#pragma unroll
            for (int ks = 1; ks < 4; ks++) {
                wg_n32_h<1, 1>(ev, af[ks], dx1 + ks * 32);
                wg_n32_h<1, 1>(od, af[4 + ks], dx1 + 256 + ks * 32);
            }
            wg_commit();
            wg_wait<0>();
#pragma unroll
            for (int i = 0; i < 8; i++) af[i] = ld_tab(TOFF_A4 + (i * 128 + tl) * 4);
            uint32_t a2[4][4];
#pragma unroll
            for (int j = 0; j < 4; j++)
#pragma unroll
                for (int h = 0; h < 2; h++) {
                    float pr[2], pi[2];
#pragma unroll
                    for (int e = 0; e < 2; e++) {
                        const float yr = h ? ev[4 * j + e] - od[4 * j + e] : ev[4 * j + e] + od[4 * j + e];
                        const float yi = h ? ev[4 * j + 2 + e] - od[4 * j + 2 + e] : ev[4 * j + 2 + e] + od[4 * j + 2 + e];
                        const float c = __uint_as_float(e ? tw[2 * j + h].z : tw[2 * j + h].x), s = __uint_as_float(e ? tw[2 * j + h].w : tw[2 * j + h].y);
                        pr[e] = fmaf(yr, c, yi * s);
                        pi[e] = fmaf(yi, c, -yr * s);
                    }
                    a2[j >> 1][(j & 1) * 2 + h] = pack_h2(pr[0], pr[1]);
                    a2[2 + (j >> 1)][(j & 1) * 2 + h] = pack_h2(pi[0], pi[1]);
                }
            TS(1, 1, tid == 0);
            float acc[32];
            wg_fence();
            wg_n64_h<0, 0>(acc, make_uint4(a2[0][0], a2[0][1], a2[0][2], a2[0][3]), dg);
#pragma unroll
            for (int ks = 1; ks < 4; ks++) wg_n64_h<0, 1>(acc, make_uint4(a2[ks][0], a2[ks][1], a2[ks][2], a2[ks][3]), dg + ks * 2);
            wg_commit();
            uint4 wv[4];
            const uint32_t wa = sb + SM_Z + q * 8192 + tl * 64;
            mbar_wait(bar + 8 * (B_WF0 + q), 0);
#pragma unroll
            for (int j = 0; j < 4; j++) wv[j] = lds128(wa + ((j ^ ((tl >> 1) & 3)) << 4));
            if (((wv[0].x ^ TAG) | (wv[1].x ^ TAG) | (wv[2].x ^ TAG) | (wv[3].x ^ TAG)) & 1) {
                const int bpc = ((cpos >> 6) + 1) & 3, kcol = apc < 32 ? 7 * apc + bpc : 448 - 7 * apc - bpc;
                const uint32_t* wp = g_Wt + (size_t)kcol * 2048 + tl * 16;
                RETRY(1);
#pragma unroll 1
                for (int j = 0; j < 4; j++) {
                    uint4 v;
                    int att = 0;
                    do {
                        asm volatile("ld.relaxed.gpu.global.v4.b32 {%0,%1,%2,%3}, [%4];" : "=r"(v.x), "=r"(v.y), "=r"(v.z), "=r"(v.w) : "l"(wp + j * 4) : "memory");
                    } while (((v.x ^ TAG) & 1) && ++att < 1000000);
                    sts128(wa + j * 16, v.x, v.y, v.z, v.w);
                }
#pragma unroll
                for (int j = 0; j < 4; j++) wv[j] = lds128(wa + ((j ^ ((tl >> 1) & 3)) << 4));
            }
            __syncwarp();
#pragma unroll
            for (int j = 0; j < 4; j++) wv[j].x &= ~1u;
            wg_wait<0>();
            TS(1, 2, tid == 0);
#pragma unroll
            for (int j = 0; j < 4; j++)
#pragma unroll
                for (int h = 0; h < 2; h++) {
                    float zr[2], zi[2];
#pragma unroll
                    for (int e = 0; e < 2; e++) {
                        const uint32_t wq = h ? (e ? wv[j].w : wv[j].z) : (e ? wv[j].y : wv[j].x);
                        const float wre = bf_lo(wq), wim = bf_hi(wq);
                        const float xr_ = acc[4 * j + 2 * h + e], xi_ = acc[16 + 4 * j + 2 * h + e];
                        zr[e] = fmaf(xr_, wre, -xi_ * wim);
                        zi[e] = fmaf(xr_, wim, xi_ * wre);
                    }
                    a2[j >> 1][(j & 1) * 2 + h] = pack_b2(zr[0], zr[1]);
                    a2[2 + (j >> 1)][(j & 1) * 2 + h] = pack_b2(zi[0], zi[1]);
                }
            wg_fence();
            wg_n64_b<0, 0>(acc, make_uint4(a2[0][0], a2[0][1], a2[0][2], a2[0][3]), dg + 512);
#pragma unroll
            for (int ks = 1; ks < 4; ks++) wg_n64_b<0, 1>(acc, make_uint4(a2[ks][0], a2[ks][1], a2[ks][2], a2[ks][3]), dg + 512 + ks * 2);
            wg_commit();
            wg_wait<0>();
            TS(1, 3, tid == 0);
#pragma unroll
            for (int h = 0; h < 2; h++) {
                uint32_t pr[4], pi[4];
#pragma unroll
                for (int j = 0; j < 4; j++) {
                    float vr[2], vi[2];
#pragma unroll
                    for (int e = 0; e < 2; e++) {
                        const float c = __uint_as_float(e ? tw[2 * j + h].z : tw[2 * j + h].x), s = __uint_as_float(e ? tw[2 * j + h].w : tw[2 * j + h].y);
                        const float ur = acc[4 * j + 2 * h + e], ui = acc[16 + 4 * j + 2 * h + e];
                        vr[e] = fmaf(ur, c, -ui * s);
                        vi[e] = fmaf(ui, c, ur * s);
                    }
                    pr[j] = pack_b2(vr[0], vr[1]);
                    pi[j] = pack_b2(vi[0], vi[1]);
                }
                const int al = 4 * w + (g & 3) + 16 * h;
                const uint32_t dsta = xa + (g >> 2) * 4096 + al * 64 + ((t ^ ((al >> 1) & 3)) << 4);
                sts128(dsta, pr[0], pr[1], pr[2], pr[3]);
                sts128(dsta + 2048, pi[0], pi[1], pi[2], pi[3]);
            }
            fence_async_smem();
            if (q) bar_sync<3, 128>(); else bar_sync<2, 128>();
            TS(1, 4, tid == 0);
            wg_fence();
            wg_n32_b<1, 0>(ev, af[0], dx);
            wg_n32_b<1, 0>(od, af[4], dx + 256);
#pragma unroll
            for (int ks = 1; ks < 4; ks++) {
                wg_n32_b<1, 1>(ev, af[ks], dx + ks * 64);
                wg_n32_b<1, 1>(od, af[4 + ks], dx + 256 + ks * 64);
            }
            wg_commit();
            const uint32_t dst = sb + SM_T + tl * 64 + (((2 * q) ^ ((tl >> 1) & 3)) << 4);
            wg_wait<0>();
            TS(1, 5, tid == 0);
#pragma unroll
            for (int ri = 0; ri < 2; ri++) {
                const int o = 2 * ri;
                uint32_t zp[4], zm[4];
#pragma unroll
                for (int j = 0; j < 4; j++) {
                    zp[j] = pack_b2(ev[o + 4 * j] + od[o + 4 * j], ev[o + 4 * j + 1] + od[o + 4 * j + 1]);
                    zm[j] = pack_b2(ev[o + 4 * j] - od[o + 4 * j], ev[o + 4 * j + 1] - od[o + 4 * j + 1]);
                    {
                        const uint32_t tm = ((cpos >> 2) & 3) == j;
                        zp[j] = tagw(zp[j], ~tm, tm & TAG);
                        zm[j] = tagw(zm[j], ~tm, tm & TAG);
                    }
                }
                sts128(dst ^ (ri * 16), zp[0], zp[1], zp[2], zp[3]);
                sts128((dst ^ (ri * 16)) + 8192, zm[0], zm[1], zm[2], zm[3]);
            }
            fence_async_smem();
        }
        if (cta < 113) {
            if (warp == 0) {
                bar_sync<1, 256>();
                TS(1, 6, tid == 0);
                if (elect_one()) {
                    tma_st_2d(&tmz, sb + SM_T, cpos * 8, 0);
                    store_issued();
                    bump(&g_cnt[C_Z * 64]);
                    TS(1, 7, true);
                }
                __syncwarp();
            } else {
                bar_arrive<1, 256>();
            }
        }
        {
            uint4 af[8];
#pragma unroll
            for (int i = 0; i < 8; i++) af[i] = ld_tab(TOFF_A3 + (i * 128 + tl) * 4);
            const uint4 t0 = ld_tab(TOFF_TW3 + (8 * w + g) * 12), t1 = ld_tab(TOFF_TW3 + (8 * w + g) * 12 + 4), t2 = ld_tab(TOFF_TW3 + (8 * w + g) * 12 + 8);
            const float twc[2][3] = {{__uint_as_float(t0.x), __uint_as_float(t0.z), __uint_as_float(t1.x)},
                                     {__uint_as_float(t1.z), __uint_as_float(t2.x), __uint_as_float(t2.z)}};
            const float tws[2][3] = {{__uint_as_float(t0.y), __uint_as_float(t0.w), __uint_as_float(t1.y)},
                                     {__uint_as_float(t1.w), __uint_as_float(t2.y), __uint_as_float(t2.w)}};
            const uint32_t za = sb + SM_Z + q * 8192;
            if (tl < 62) sts128(za + 6144 + (tl < 30 ? 544 : 1056) + tl * 16, 0, 0, 0, 0);
            fence_async_smem();
            float xf[2][2][7], xs[2];
            {
                mbar_wait(bar + 8 * B_XS, 0);
                const uint32_t xa = sb + SM_XS + (8 * q + (lane & 7)) * XS_PITCH + w * 16;
                uint32_t p[16];
#pragma unroll
                for (int i = 0; i < 3; i++) ldsm4t(xa + (lane >> 3) * 64 + i * 256, p[4 * i], p[4 * i + 1], p[4 * i + 2], p[4 * i + 3]);
                ldsm2t(xa + ((lane >> 3) & 1) * 64 + 768, p[12], p[13]);
#pragma unroll
                for (int m = 0; m < 7; m++)
#pragma unroll
                    for (int hi = 0; hi < 2; hi++) {
                        xf[hi][0][m] = bf_lo(p[2 * m + hi]);
                        xf[hi][1][m] = bf_hi(p[2 * m + hi]);
                    }
#pragma unroll
                for (int e = 0; e < 2; e++) {
                    xs[e] = 0.f;
#pragma unroll
                    for (int m = 0; m < 7; m++) xs[e] += xf[0][e][m] + xf[1][e][m];
                    asm volatile("" : "+f"(xs[e]));
                }
            }
            const uint64_t dz = mk_desc(za, 128, 2048, 0);
            {
                mbar_wait(bar + 8 * (B_Z + q), 0);
                TS(2, 0, tid == 0);
                if (check_chunks(za + tl * 16, g_Z + (size_t)cta * ZSTRIDE + q * 8192 + tl * 16, (lane >> 3) & 3, TAG, tl < 34 || (tl >= 64 && tl < 96))) RETRY(2);
                if (q) bar_sync<3, 128>(); else bar_sync<2, 128>();
            }
            float ev[16], od[16];
            wg_fence();
            wg_n32_b<1, 0>(ev, af[0], dz);
            wg_n32_b<1, 0>(od, af[4], dz + 64);
#pragma unroll
            for (int ks = 1; ks < 4; ks++) {
                wg_n32_b<1, 1>(ev, af[ks], dz + ks * 16);
                wg_n32_b<1, 1>(od, af[4 + ks], dz + 64 + ks * 16);
            }
            wg_commit();
            wg_wait<0>();
            TS(2, 1, tid == 0);
            float st[4];
#pragma unroll
            for (int e = 0; e < 2; e++) {
                float ss = 0.f;
#pragma unroll
                for (int hi = 0; hi < 2; hi++) {
                    const float u0 = (hi ? ev[12 + e] - od[12 + e] : ev[12 + e] + od[12 + e]) * (1.f / 7.f);
                    float pr[3], pi[3];
#pragma unroll
                    for (int b = 0; b < 3; b++) {
                        const float ur = hi ? ev[4 * b + e] - od[4 * b + e] : ev[4 * b + e] + od[4 * b + e];
                        const float ui = hi ? ev[4 * b + 2 + e] - od[4 * b + 2 + e] : ev[4 * b + 2 + e] + od[4 * b + 2 + e];
                        pr[b] = fmaf(ur, twc[hi][b], -ui * tws[hi][b]);
                        pi[b] = fmaf(ui, twc[hi][b], ur * tws[hi][b]);
                    }
                    float(&y)[7] = xf[hi][e];
                    const float e1 = fmaf(C3, pr[2], fmaf(C2, pr[1], fmaf(C1, pr[0], u0)));
                    const float e2 = fmaf(C1, pr[2], fmaf(C3, pr[1], fmaf(C2, pr[0], u0)));
                    const float e3 = fmaf(C2, pr[2], fmaf(C1, pr[1], fmaf(C3, pr[0], u0)));
                    const float o1 = fmaf(S3, pi[2], fmaf(S2, pi[1], S1 * pi[0]));
                    const float o2 = fmaf(-S1, pi[2], fmaf(-S3, pi[1], S2 * pi[0]));
                    const float o3 = fmaf(S2, pi[2], fmaf(-S1, pi[1], S3 * pi[0]));
                    y[0] += (u0 + pr[0]) + (pr[1] + pr[2]);
                    y[1] += e1 - o1;
                    y[6] += e1 + o1;
                    y[2] += e2 - o2;
                    y[5] += e2 + o2;
                    y[3] += e3 - o3;
                    y[4] += e3 + o3;
#pragma unroll
                    for (int m = 0; m < 7; m++) ss = fmaf(y[m], y[m], ss);
                }
                st[e] = fmaf(2.f, ev[12 + e], xs[e]);
                st[2 + e] = ss;
            }
            {
                const bool b2_ = lane & 16, b1_ = lane & 8;
#pragma unroll
                for (int i = 0; i < 2; i++) {
                    const float snd = b2_ ? st[i] : st[i + 2], keep = b2_ ? st[i + 2] : st[i];
                    st[i] = keep + __shfl_xor_sync(0xffffffffu, snd, 16);
                }
                const float snd = b1_ ? st[0] : st[1], keep = b1_ ? st[1] : st[0];
                float v = keep + __shfl_xor_sync(0xffffffffu, snd, 8);
                v += __shfl_xor_sync(0xffffffffu, v, 4);
                if (!(lane & 4)) sts32(sb + SM_RED + q * 256 + (t * 4 + ((lane >> 3) & 1) * 2 + (lane >> 4)) * 16 + w * 4, __float_as_uint(v));
            }
            if (q) bar_sync<3, 128>(); else bar_sync<2, 128>();
            TS(2, 2, tid == 0);
            float scl[2], off[2];
            uint8_t* hp = g_hn + (size_t)(cta * 2 + q) * 1792 + (8 * w + g) * 16 + t * 4;
            uint8_t* hp2 = hp + (w >= 2 ? 256 * 1792 - 1792 : 0);
            {
                uint4 rv[4];
#pragma unroll
                for (int i = 0; i < 4; i++) rv[i] = lds128(sb + SM_RED + q * 256 + (t * 4 + i) * 16);
#pragma unroll
                for (int e = 0; e < 2; e++) {
                    const uint4 a = rv[2 * e], b = rv[2 * e + 1];
                    const float sm = (__uint_as_float(a.x) + __uint_as_float(a.y)) + (__uint_as_float(a.z) + __uint_as_float(a.w));
                    const float sq = (__uint_as_float(b.x) + __uint_as_float(b.y)) + (__uint_as_float(b.z) + __uint_as_float(b.w));
                    const float mean = sm * (1.f / 448.f);
                    const float var = fmaxf(fmaf(-mean, mean, sq * (1.f / 448.f)), 0.f);
                    const float den = fmaf(1e-5f, var + 1e-5f, var);
                    scl[e] = rsqrtf(den);
                    off[e] = -mean * scl[e];
                    if (tl < 4) scr->rs[cta * 16 + 8 * q + 2 * t + e] = make_float2(den * scl[e], mean);
                }
            }
#pragma unroll
            for (int m = 0; m < 7; m++)
#pragma unroll
                for (int hi = 0; hi < 2; hi++)
                {
                    constexpr int TSTR = 256 * 1792 - 1792;
                    const int j = 2 * m + hi;
                    uint8_t* pj = ((j == 3 || j == 10) ? hp2 : hp) + j * 512 + (j < 4 ? 0 : j < 7 ? 1 : j < 11 ? 2 : 3) * TSTR;
                    stg32(pj, pack_b2(fmaf(xf[hi][0][m], scl[0], off[0]), fmaf(xf[hi][1][m], scl[1], off[1])));
                }
            bar_arrive<5, 288>();
            TS(2, 3, tid == 0);
        }
        {
        int tid2;
        asm volatile("mov.u32 %0, %%tid.x;" : "=r"(tid2));
        const int lane = tid2 & 31, g = lane >> 2, t = lane & 3, tl = tid2 & 127;
        if (g1_half) {
            const int mrow = mt1 * 64 + w * 16 + 8 * q + g;
            const float bv = __bfloat162float(b1[mrow]);
            uint8_t* dst = g_g + (size_t)(dt * 28 + mt1) * AB + ((cta >> 4) & 1) * 7168 + (mrow & 63) * 16 + t * 4;
            float acc[28];
            gemm_half(acc, sb, q);
            const uint32_t xo = sb + SM_A + (6 + q) * AB + tl * 8, xi = sb + SM_A + (7 - q) * AB + tl * 8;
            if (q) bar_sync<3, 128>(); else bar_sync<2, 128>();
#pragma unroll
            for (int j = 0; j < 7; j++) sts64(xo + j * 1024, __float_as_uint(q ? acc[4 * j] : acc[4 * j + 2]), __float_as_uint(q ? acc[4 * j + 1] : acc[4 * j + 3]));
            bar_sync<1, 256>();
#pragma unroll
            for (int j = 0; j < 7; j++) {
                float p0, p1;
                asm volatile("ld.shared.v2.f32 {%0,%1}, [%2];" : "=f"(p0), "=f"(p1) : "r"(xi + j * 1024) : "memory");
                stg32(dst + j * 1024, max(pack_b2(gelu_tanh((q ? acc[4 * j + 2] : acc[4 * j]) + p0 + bv), gelu_tanh((q ? acc[4 * j + 3] : acc[4 * j + 1]) + p1 + bv)), 1u));
            }
            bar_arrive<8, 288>();
            if (elect_one()) mbar_arrive(bar + 8 * (B_AEMPTY + 7 - q));
            TS(3, 6, tid == 0);
        }
        if (q == 0) {
            if (!g1_half) {
                const int mrow = mt1 * 64 + w * 16 + g;
                const float bv0 = __bfloat162float(b1[mrow]), bv1 = __bfloat162float(b1[mrow + 8]);
                uint8_t* dst = g_g + (size_t)(dt * 28 + mt1) * AB + (mrow & 63) * 16 + t * 4;
                float acc[56];
#pragma unroll
                for (int i = 0; i < 56; i++) acc[i] = (i & 2) ? bv1 : bv0;
                gemm_loop<0>(acc, sb, 0, 0, 16);
                bar_arrive<7, 256>();
                TS(3, 1, tid == 0);
#pragma unroll
                for (int j = 0; j < 14; j++) {
                    stg32(dst + j * 1024, max(pack_b2(gelu_tanh(acc[4 * j]), gelu_tanh(acc[4 * j + 1])), 1u));
                    stg32(dst + j * 1024 + 128, max(pack_b2(gelu_tanh(acc[4 * j + 2]), gelu_tanh(acc[4 * j + 3])), 1u));
                }
                TS(3, 2, tid == 0);
                bar_arrive<6, 160>();
            }
#pragma unroll 1
            for (int i = 4; i < 8; i++) {
                mbar_wait(bar + 8 * (B_EARLY + i), 0);
                const uint32_t sa = sb + SM_A + ((2 + i) & 7) * AB + tl * 16;
                uint32_t c[7];
#pragma unroll
                for (int j = 0; j < 7; j++) c[j] = lds32(sa + (lane >> 3) * 4 + j * 2048);
                if (!(c[0] && c[1] && c[2] && c[3] && c[4] && c[5] && c[6])) {
                    patch_zero(sa, g_g + (size_t)(dt * 28 + i) * AB + tl * 16);
                    RETRY(3);
                }
                bar_sync<2, 128>();
                if (tl == 0) mbar_arrive(bar + 8 * (B_AFULL + ((2 + i) & 7)));
                TS(4, 6, tl == 0 && i == 4);
            }
        } else {
            const int srow = (cta >> 2) * 64 + w * 16;
            const float bv0 = __bfloat162float(b2[srow + g]), bv1 = __bfloat162float(b2[srow + g + 8]);
            constexpr int i0 = 32;
            float acc[56];
            {
                mbar_wait(bar + 8 * B_RES, 0);
                float2 r0, r1;
                asm volatile("ld.relaxed.gpu.global.v2.f32 {%0,%1}, [%2];" : "=f"(r0.x), "=f"(r0.y) : "l"(&scr->rs[srow + g]) : "memory");
                asm volatile("ld.relaxed.gpu.global.v2.f32 {%0,%1}, [%2];" : "=f"(r1.x), "=f"(r1.y) : "l"(&scr->rs[srow + g + 8]) : "memory");
                r0.y += bv0;
                r1.y += bv1;
                const uint32_t ha = sb + SM_A + (2 * w + ((lane >> 3) & 1)) * 1792 + (lane >> 4) * 128 + (lane & 7) * 16;
#pragma unroll
                for (int i = 0; i < 7; i++) {
                    uint32_t h0, h1, h2, h3;
                    ldsm4t(ha + i * 256, h0, h1, h2, h3);
                    acc[8 * i] = fmaf(bf_lo(h0), r0.x, r0.y);
                    acc[8 * i + 1] = fmaf(bf_hi(h0), r0.x, r0.y);
                    acc[8 * i + 2] = fmaf(bf_lo(h1), r1.x, r1.y);
                    acc[8 * i + 3] = fmaf(bf_hi(h1), r1.x, r1.y);
                    acc[8 * i + 4] = fmaf(bf_lo(h2), r0.x, r0.y);
                    acc[8 * i + 5] = fmaf(bf_hi(h2), r0.x, r0.y);
                    acc[8 * i + 6] = fmaf(bf_lo(h3), r1.x, r1.y);
                    acc[8 * i + 7] = fmaf(bf_hi(h3), r1.x, r1.y);
                }
                __syncwarp();
                if (elect_one()) {
                    mbar_arrive(bar + 8 * B_AEMPTY);
                    mbar_arrive(bar + 8 * (B_AEMPTY + 1));
                }
            }
            uint8_t* ob = reinterpret_cast<uint8_t*>(out) + (size_t)(srow + (lane >> 4)) * 896 + dt * 224 + (lane & 15) * 16;
#pragma unroll 1
            for (int i = 0; i < 4; i++) {
                mbar_wait(bar + 8 * (B_EARLY + i), 0);
                const uint32_t sa = sb + SM_A + (2 + i) * AB + tl * 16;
                uint32_t c[7];
#pragma unroll
                for (int j = 0; j < 7; j++) c[j] = lds32(sa + (lane >> 3) * 4 + j * 2048);
                if (!(c[0] && c[1] && c[2] && c[3] && c[4] && c[5] && c[6])) {
                    patch_zero(sa, g_g + (size_t)(dt * 28 + i) * AB + tl * 16);
                    RETRY(3);
                }
            }
            if (!g1_half) bar_sync<7, 256>(); else bar_sync<3, 128>();
            if (tl < 4) mbar_arrive(bar + 8 * (B_AFULL + 2 + tl));
            TS(4, 4, tl == 0);
            gemm_loop<1>(acc, sb, i0, i0 + 2, 14);
            TS(4, 1, tl == 0);
            const uint32_t stg = sb + SM_A + 6 * AB + w * 4096;
#pragma unroll
            for (int i = 0; i < 7; i++)
                stsm4(stg + (lane & 15) * 240 + (lane >> 4) * 16 + i * 32, pack_b2(acc[8 * i], acc[8 * i + 1]), pack_b2(acc[8 * i + 2], acc[8 * i + 3]),
                      pack_b2(acc[8 * i + 4], acc[8 * i + 5]), pack_b2(acc[8 * i + 6], acc[8 * i + 7]));
            __syncwarp();
            if ((lane & 15) < 14) {
                uint4 o4[8];
#pragma unroll
                for (int i = 0; i < 8; i++) o4[i] = lds128(stg + (2 * i + (lane >> 4)) * 240 + (lane & 15) * 16);
#pragma unroll
                for (int i = 0; i < 8; i++) stg128(ob + i * 1792, o4[i]);
            }
            TS(4, 2, tl == 0);
        }
        }
        {
        }
    } else {
    if (warp == 8) {
        asm volatile("ld.relaxed.gpu.global.u32 %0, [%1];" : "=r"(tag) : "l"(&scr->epoch) : "memory");
        if (elect_one()) {
#pragma unroll
            for (int i = 0; i <= B_XS; i++) {
                const bool empty = (i >= B_WEMPTY && i < B_AFULL) || (i >= B_AEMPTY && i < B_X0);
                mbar_init(bar + 8 * i, empty ? 4 : 1);
            }
            asm volatile("fence.mbarrier_init.release.cluster;" ::: "memory");
            fence_async_smem();
        }
        if (cta == 0) {
#pragma unroll
            for (int i = C_Z; i < 28; i++) g_cnt[i * 64 + lane] = 0;
            __threadfence();
        }
        sts32(bar + 632, tag);
        __syncwarp();
        bar_arrive<11, 288>();
        bar_arrive<12, 128>();
        if (elect_one()) {
            asm volatile("prefetch.tensormap [%0];" ::"l"(&tmx) : "memory");
            asm volatile("prefetch.tensormap [%0];" ::"l"(&tmw) : "memory");
            asm volatile("prefetch.tensormap [%0];" ::"l"(&tmz) : "memory");
            asm volatile("prefetch.tensormap [%0];" ::"l"(&tm1) : "memory");
            asm volatile("prefetch.tensormap [%0];" ::"l"(&tm2) : "memory");
            asm volatile("prefetch.tensormap [%0];" ::"l"(&tmh) : "memory");
            mbar_expect(bar + 8 * B_G, 16384);
            bulk_g2s(sb + SM_G, tab + TOFF_G, 16384, bar + 8 * B_G);
            if (cta < 4) l2_prefetch(tab + TOFF_A2 + cta * 4096, 16384 + (cta == 3 ? 1536 : 0));
            const uint8_t* xs[2];
#pragma unroll
            for (int q = 0; q < 2; q++) {
                const int cpos = max(col_pos(cta, q), 0);
                xs[q] = g_X + (size_t)((cpos & ~63) + 2 * (cpos & 31) + ((cpos >> 5) & 1)) * 8192;
                mbar_expect(bar + 8 * (B_X0 + q), 8192);
                mbar_expect(bar + 8 * (B_Z + q), 7200);
            }
            const int hx = ((cta >> 4) & 1) * 112, hy = dt * 256;
#pragma unroll
            for (int i = 0; i < AS; i++) mbar_expect(bar + 8 * (B_AFULL + i), AB);
            const uint8_t* zs = g_Z + (size_t)cta * ZSTRIDE;
            const uint8_t* hs = g_hn + (size_t)dt * 32 * AB;
            hint_poll(&g_cnt[C_X * 64], NCTA);
            if (cta < 113) {
                bulk_g2s(sb + SM_X, xs[0], 8192, bar + 8 * B_X0);
                bulk_g2s(sb + SM_X + 8192, xs[1], 8192, bar + 8 * (B_X0 + 1));
            }
            TS(0, 7, true);
            mbar_arrive(bar + 8 * B_EV);
            hint_poll(&g_cnt[C_Z * 64], 113);
            bulk_g2s(sb + SM_Z, zs, 6688, bar + 8 * B_Z);
            bulk_g2s(sb + SM_Z + 8192, zs + 8192, 6688, bar + 8 * (B_Z + 1));
            bulk_g2s(sb + SM_Z + 7168, zs + 7168, 512, bar + 8 * B_Z);
            bulk_g2s(sb + SM_Z + 8192 + 7168, zs + 8192 + 7168, 512, bar + 8 * (B_Z + 1));
            TS(2, 5, true);
            mbar_arrive(bar + 8 * (B_EV + 1));
            int st = 0, ph = 1;
            mbar_wait(bar + 8 * B_OWN, 0);
            cnt_wait_r(&g_cnt[(g1_half ? C_H : C_H0) * 64], g1_half ? NCTA : 4 * AS);
            if (g1_half) {
#pragma unroll
                for (int i = 0; i < AS; i++) tma_2d(sb + SM_A + i * AB, &tmh, hx, hy + i * 16, bar + 8 * (B_AFULL + i));
            } else {
#pragma unroll
                for (int i = 0; i < AS; i++) bulk_g2s(sb + SM_A + i * AB, hs + i * AB, AB, bar + 8 * (B_AFULL + i));
            }
            TS(3, 0, true);
            mbar_arrive(bar + 8 * (B_EV + 2));
            cnt_wait_r(&g_cnt[C_H * 64], NCTA);
            if (cta == 0) {
#pragma unroll
                for (int i = 0; i < REPL; i++) { g_cnt[(C_X + i) * 64] = 0; g_cnt[(C_W + i) * 64] = 0; }
                scr->epoch = tag + 1;
            }
            ph = 0;
#pragma unroll 1
            for (int kb = AS; kb < (g1_half ? 16 : 32); kb++) {
                mbar_wait(bar + 8 * (B_AEMPTY + st), ph);
                mbar_expect(bar + 8 * (B_AFULL + st), AB);
                if (g1_half) tma_2d(sb + SM_A + st * AB, &tmh, hx, hy + kb * 16, bar + 8 * (B_AFULL + st));
                else bulk_g2s(sb + SM_A + st * AB, hs + (size_t)kb * AB, AB, bar + 8 * (B_AFULL + st));
                if (++st == AS) { st = 0; ph ^= 1; }
            }
            static_assert(32 % AS == 0 && AS == 8, "slot bookkeeping below");
#pragma unroll
            for (int i = 0; i < 2; i++) {
                mbar_wait(bar + 8 * (B_AEMPTY + i), ph);
                mbar_arrive(bar + 8 * (B_AFULL + i));
            }
            mbar_expect(bar + 8 * B_RES, AB);
            bulk_g2s(sb + SM_A, hs + (size_t)(cta >> 2) * AB, AB, bar + 8 * B_RES);
            const uint8_t* gs = g_g + (size_t)dt * 28 * AB;
#pragma unroll
            for (int i = 0; i < 8; i++) mbar_expect(bar + 8 * (B_EARLY + i), AB);
            cnt_wait(&g_cnt[(C_G0 + dt) * 64], 8);
            TS(4, 3, true);
#pragma unroll
            for (int i = 2; i < 8; i++) {
                mbar_wait(bar + 8 * (B_AEMPTY + i), ph);
                if (i < 6) bulk_g2s(sb + SM_A + i * AB, gs + (i - 2) * AB, AB, bar + 8 * (B_EARLY + i - 2));
            }
            ph ^= 1;
            mbar_wait2(bar + 8 * B_AEMPTY, ph, bar + 8 * (B_AEMPTY + 1), ph);
            cnt_wait(&g_cnt[(C_G1 + dt) * 64], 4);
#pragma unroll
            for (int i = 4; i < 8; i++) bulk_g2s(sb + SM_A + ((2 + i) & 7) * AB, gs + i * AB, AB, bar + 8 * (B_EARLY + i));
            TS(4, 5, true);
            cnt_wait(&g_cnt[(C_G + dt) * 64], 20);
            TS(4, 0, true);
            st = 2;
#pragma unroll 1
            for (int kb = 8; kb < 28; kb++) {
                mbar_wait(bar + 8 * (B_AEMPTY + st), ph);
                mbar_expect(bar + 8 * (B_AFULL + st), AB);
                bulk_g2s(sb + SM_A + st * AB, gs + (size_t)kb * AB, AB, bar + 8 * (B_AFULL + st));
                if (++st == AS) { st = 0; ph ^= 1; }
            }
        }
    } else {
        {
            const int w = cta >> 5, g = (cta >> 2) & 7, t = cta & 3;
            const int o = g >> 2;
            const int p = lane & 1, wl = (warp - 9) * 16 + (lane >> 1);
            uint32_t vr[3][8], vi[3][8];
            spin_until(clk32() + W_DELAY);
            const int e0 = (8 * w + 2 * (g & 3) + o + 64 * (8 * p + 2 * t)) * DF_ - o + 2 * wl;
            const uint32_t* pr = reinterpret_cast<const uint32_t*>(wr + e0);
            const uint32_t* pi = reinterpret_cast<const uint32_t*>(wi + e0);
#pragma unroll
            for (int it = 0; it < 3; it++) {
#pragma unroll
                for (int i = 0; i < 8; i++) {
                    const int off = (32 * ((i >> 1) & 1) + 64 * (i & 1) + 1024 * (i >> 2)) / 2 * DF_ + 48 * it;
                    vr[it][i] = 0; vi[it][i] = 0;
                    if (it < 2 || wl < 17) {
                        asm volatile("ld.global.nc.b32 %0, [%1];" : "=r"(vr[it][i]) : "l"(pr + off) : "memory");
                        asm volatile("ld.global.nc.b32 %0, [%1];" : "=r"(vi[it][i]) : "l"(pi + off) : "memory");
                    }
                }
            }
            bar_sync<12, 128>();
            tag = lds32(bar + 632);
            const int sw = (cta >> 1) & 3;
#pragma unroll
            for (int it = 0; it < 3; it++) {
                const int c = wl + 48 * it;
#pragma unroll
                for (int u = 0; u < 2; u++) {
                    const int k = 2 * c + u - o;
                    if ((it + u > 0 || k >= 0) && (it < 2 || k < DF_)) {
                        uint32_t z[8];
#pragma unroll
                        for (int i = 0; i < 8; i++) z[i] = __byte_perm(vr[it][i], vi[it][i], u ? 0x7632 : 0x5410);
                        const uint32_t dst = sb + SM_WF + k * 64;
                        sts128(dst + ((p ^ sw) << 4), tagw(z[0], ~1u, TAG), z[1], z[2], z[3]);
                        sts128(dst + (((2 + p) ^ sw) << 4), tagw(z[4], ~1u, TAG), z[5], z[6], z[7]);
                    }
                }
            }
            fence_async_smem();
        }
        TS(0, 5, tid == 288);
        if (warp == 10) {
            bar_sync<10, 96>();
            if (elect_one()) {
                mbar_wait(bar + 8 * B_GO, 0);
                tma_st_2d(&tmw, sb + SM_WF, cta * 16, 0);
                store_issued();
                bump(&g_cnt[C_W * 64]);
                TS(3, 4, true);
                if (cta < 113) {
                    hint_poll(&g_cnt[C_W * 64], NCTA);
                    TS(3, 5, true);
#pragma unroll
                    for (int q = 0; q < 2; q++) {
                        const int cpos = col_pos(cta, q);
                        const int ap = 2 * (cpos & 31) + ((cpos >> 5) & 1), bp = ((cpos >> 6) + 1) & 3;
                        if (cpos >= 0) {
                            mbar_expect(bar + 8 * (B_WF0 + q), 8192);
                            bulk_g2s(sb + SM_Z + q * 8192, g_Wt + (size_t)(ap < 32 ? 7 * ap + bp : 448 - 7 * ap - bp) * 2048, 8192, bar + 8 * (B_WF0 + q));
                        }
                    }
                }
                mbar_wait(bar + 8 * (B_EV + 1), 0);
                uint32_t tp = clk32() + EV_DELAY;
                if (cta < 112) {
#pragma unroll 1
                    for (int i = 0; i < 5; i++) {
                        pace_until(tp);
                        tp += PACE_PF1;
                        if (WS + dt + 4 * i < 32) tma_pf_2d(&tm1, mt1 * 64, (WS + dt + 4 * i) * 64);
                    }
                }
                mbar_wait(bar + 8 * (B_EV + 2), 0);
                tp = clk32() + EV_DELAY;
                const char* p2 = reinterpret_cast<const char*>(w2) + (size_t)cta * 57344;
#pragma unroll 1
                for (int u = 0; u < 7; u++) {
                    pace_until(tp);
                    tp += PACE_PF;
                    l2_prefetch(p2 + u * 8192, 8192);
                }
            }
        } else {
            bar_arrive<10, 96>();
            if (warp == 11) {
                if (elect_one()) {
                    mbar_wait(bar + 8 * B_EV, 0);
                    pace_until(clk32() + EV_DELAY);
                    mbar_expect(bar + 8 * B_XS, 16 * 896);
                    for (int i = 0; i < 16; i++) bulk_g2s(sb + SM_XS + i * XS_PITCH, x + (size_t)(cta * 16 + i) * D_, 896, bar + 8 * B_XS);
                }
                __syncwarp();
                if (mt1 < 8) {
                    pace_until(clk32() + ZDELAY);
                    uint8_t* gz = g_g + (size_t)(dt * 28 + mt1) * AB + (g1_half ? ((cta >> 4) & 1) * 7168 : 0) + lane * 16;
#pragma unroll 2
                    for (int i = 0; i < (g1_half ? 14 : 28); i++) stg128(gz + i * 512, make_uint4(0, 0, 0, 0));
                }
                bar_sync<5, 288>();
                if (elect_one()) {
                    mbar_arrive(bar + 8 * B_OWN);
                    asm volatile("fence.acq_rel.gpu;" ::: "memory");
                    if (cta < 4 * AS) bump(&g_cnt[C_H0 * 64]);
                    bump(&g_cnt[C_H * 64]);
                    TS(2, 4, true);
                }
                __syncwarp();
                if (g1_half) bar_sync<8, 288>(); else bar_sync<6, 160>();
                if (elect_one()) {
                    if (mt1 < 8) asm volatile("red.relaxed.gpu.global.add.u32 [%0], 1;" ::"l"(&g_cnt[((g1_half ? C_G0 : C_G1) + dt) * 64]) : "memory");
                    else asm volatile("red.release.gpu.global.add.u32 [%0], 1;" ::"l"(&g_cnt[(C_G + dt) * 64]) : "memory");
                    TS(3, 3, !g1_half);
                }
            }
            if (warp == 9) {
                if (elect_one()) {
                    int st = 0, ph = 1;
                    mbar_wait(bar + 8 * B_EV, 0);
                    uint32_t tp = clk32() + EV_DELAY;
                    pace_until(tp);
                    constexpr int n1 = 32;
                    const int m1 = mt1 * 64, m2 = (cta >> 2) * 64;
#pragma unroll 1
                    for (int i = 0; i < n1 + 28; i++) {
                        mbar_wait(bar + 8 * (B_WEMPTY + st), ph);
                        mbar_expect(bar + 8 * (B_WFULL + st), WB);
                        if (i < n1) tma_2d(sb + SM_W + st * WB, &tm1, m1, i * 64, bar + 8 * (B_WFULL + st));
                        else tma_2d(sb + SM_W + st * WB, &tm2, m2, (i - n1) * 64, bar + 8 * (B_WFULL + st));
                        if (++st == WS) { st = 0; ph ^= 1; }
                        if (i < WS) { tp += PACE_RING; pace_until(tp); }
                    }
                }
            }
        }
    }
    }
}

typedef CUresult (*EncodeFn)(CUtensorMap*, CUtensorMapDataType, cuuint32_t, void*, const cuuint64_t*, const cuuint64_t*, const cuuint32_t*,
                             const cuuint32_t*, CUtensorMapInterleave, CUtensorMapSwizzle, CUtensorMapL2promotion, CUtensorMapFloatOOBfill);

void make_wmap(EncodeFn enc, CUtensorMap* tm, const void* ptr, int K, int M) {
    cuuint64_t dims[2] = {(cuuint64_t)M, (cuuint64_t)K};
    cuuint64_t strides[1] = {(cuuint64_t)M * 2};
    cuuint32_t box[2] = {64, 64};
    cuuint32_t es[2] = {1, 1};
    enc(tm, CU_TENSOR_MAP_DATA_TYPE_BFLOAT16, 2, const_cast<void*>(ptr), dims, strides, box, es, CU_TENSOR_MAP_INTERLEAVE_NONE,
        CU_TENSOR_MAP_SWIZZLE_128B, CU_TENSOR_MAP_L2_PROMOTION_L2_256B, CU_TENSOR_MAP_FLOAT_OOB_FILL_NONE);
}

void make_map(EncodeFn enc, CUtensorMap* tm, void* ptr, int rank, const cuuint64_t* dims, const cuuint64_t* strides, const cuuint32_t* box,
              CUtensorMapSwizzle swz) {
    cuuint32_t es[3] = {1, 1, 1};
    enc(tm, CU_TENSOR_MAP_DATA_TYPE_UINT32, rank, ptr, dims, strides, box, es, CU_TENSOR_MAP_INTERLEAVE_NONE, swz,
        CU_TENSOR_MAP_L2_PROMOTION_NONE, CU_TENSOR_MAP_FLOAT_OOB_FILL_NONE);
}

}

extern "C" void kernel_launch(void* const* d_in, const int* in_sizes, int n_in, void* d_out, int out_size) {
    const __nv_bfloat16* x = (const __nv_bfloat16*)d_in[0];
    const __nv_bfloat16* wr = (const __nv_bfloat16*)d_in[1];
    const __nv_bfloat16* wi = (const __nv_bfloat16*)d_in[2];
    const __nv_bfloat16* w1 = (const __nv_bfloat16*)d_in[4];
    const __nv_bfloat16* b1 = (const __nv_bfloat16*)d_in[5];
    const __nv_bfloat16* w2 = (const __nv_bfloat16*)d_in[6];
    const __nv_bfloat16* b2 = (const __nv_bfloat16*)d_in[7];
    __nv_bfloat16* out = (__nv_bfloat16*)d_out;

    static EncodeFn enc = nullptr;
    static CUtensorMap tmx, tmw, tmz, tmh;
    static Scratch* scr;
    static const uint32_t* tab;
    if (!enc) {
        void* fn = nullptr;
        cudaDriverEntryPointQueryResult qr;
        cudaGetDriverEntryPoint("cuTensorMapEncodeTiled", &fn, cudaEnableDefault, &qr);
        enc = (EncodeFn)fn;
        cudaFuncSetAttribute(fused_kernel, cudaFuncAttributeMaxDynamicSharedMemorySize, SM_TOTAL);
        cudaGetSymbolAddress((void**)&scr, g_scr);
        cudaGetSymbolAddress((void**)&tab, g_tab);
        void *px = scr->X, *pw = scr->Wt, *pz = scr->Z;
        {
            cuuint64_t d[2] = {2048, DF_}, st[1] = {8192};
            cuuint32_t b[2] = {16, DF_};
            make_map(enc, &tmx, px, 2, d, st, b, CU_TENSOR_MAP_SWIZZLE_64B);
            make_map(enc, &tmw, pw, 2, d, st, b, CU_TENSOR_MAP_SWIZZLE_NONE);
        }
        {
            cuuint64_t d[2] = {2048, 256}, st[1] = {8192};
            cuuint32_t b[2] = {16, 256};
            make_map(enc, &tmz, pz, 2, d, st, b, CU_TENSOR_MAP_SWIZZLE_64B);
        }
        {
            cuuint64_t d[2] = {224, 1024}, st[1] = {1792};
            cuuint32_t b[2] = {112, 16}, es[2] = {1, 1};
            enc(&tmh, CU_TENSOR_MAP_DATA_TYPE_UINT64, 2, scr->hn, d, st, b, es, CU_TENSOR_MAP_INTERLEAVE_NONE, CU_TENSOR_MAP_SWIZZLE_NONE,
                CU_TENSOR_MAP_L2_PROMOTION_NONE, CU_TENSOR_MAP_FLOAT_OOB_FILL_NONE);
        }
    }
    CUtensorMap tm1, tm2;
    make_wmap(enc, &tm1, w1, S_, F_);
    make_wmap(enc, &tm2, w2, F_, S_);
    cudaLaunchConfig_t cfg = {};
    cfg.gridDim = dim3(NCTA);
    cfg.blockDim = dim3(384);
    cfg.dynamicSmemBytes = SM_TOTAL;
    cfg.stream = cudaStreamPerThread;
    cudaLaunchAttribute at[1];
    at[0].id = cudaLaunchAttributeCooperative;
    at[0].val.cooperative = 1;
    cfg.attrs = at;
    cfg.numAttrs = 1;
    cudaLaunchKernelEx(&cfg, fused_kernel, x, tab, scr, wr, wi, w2, b1, b2, out, tm1, tm2, tmx, tmw, tmz, tmh);
}
```
